```python
import torch

def _softmax(x, axis=-1):
    return torch.softmax(x, dim=axis)
def _gelu(x):
    return torch.nn.functional.gelu(x, approximate="tanh")
def _silu(x):
    return torch.nn.functional.silu(x)
def _sigmoid(x):
    return torch.sigmoid(x)
def _layernorm(x, axis=-1, eps=1e-5):
    m = x.mean(dim=axis, keepdim=True)
    v = x.var(dim=axis, keepdim=True, unbiased=False)
    return (x - m) / torch.sqrt(v + eps)
def _scatter_add(tgt, idx, src, axis=0):
    return tgt.clone().index_add_(axis, idx, src)
def _segment_sum(src, seg, n):
    out = torch.zeros((n,) + src.shape[1:], dtype=src.dtype)
    return out.index_add_(0, seg, src)
def _pad(x, pw):
    flat = tuple(v for pair in reversed(pw) for v in pair)
    return torch.nn.functional.pad(x, flat)

kernel_name = 'parallel_sum__mha_block__mixer_channel_mlp__prompt'

def setup_inputs():

    _w = (lambda a: (lambda t: t.to(torch.bfloat16) if t.is_floating_point() else t)(torch.as_tensor(a)))
    def _A_setup():
        B, S, D, H = 1, 2048, 640, 32
        return {
            "x": _w((lambda *s: torch.randn(*s, dtype=torch.bfloat16) * 0.05)(B, S, D)),
            "wqkv": _w((lambda *s: torch.randn(*s, dtype=torch.bfloat16) * 0.05)(D, 3 * D)),
            "wo": _w((lambda *s: torch.randn(*s, dtype=torch.bfloat16) * 0.05)(D, D)),
        }
    _A_in = _A_setup()

    def _B_setup():
        B, S, D, F = 1, 2048, 640, 1536
        return {
            "x": _w((lambda *s: torch.randn(*s, dtype=torch.bfloat16) * 0.05)(B, S, D)),
            "w1": _w((lambda *s: torch.randn(*s, dtype=torch.bfloat16) * 3.2)(D, F) * (D ** -0.5)),
            "b1": _w((lambda *s: torch.randn(*s, dtype=torch.bfloat16) * 1.6)(F)),
            "w2": _w((lambda *s: torch.randn(*s, dtype=torch.bfloat16) * 0.1)(F, D) * (F ** -0.5)),
            "b2": _w((lambda *s: torch.randn(*s, dtype=torch.bfloat16) * 0.2)(D)),
        }
    _B_in = _B_setup()

    return {
        "A_x": _A_in["x"],
        "A_wqkv": _A_in["wqkv"],
        "A_wo": _A_in["wo"],
        "B_x": _B_in["x"],
        "B_w1": _B_in["w1"],
        "B_b1": _B_in["b1"],
        "B_w2": _B_in["w2"],
        "B_b2": _B_in["b2"],
    }

def reference(A_x, A_wqkv, A_wo, B_x, B_w1, B_b1, B_w2, B_b2):
    def _A_ref(x, wqkv, wo):
        B, S, D = x.shape
        H = 32
        Dh = D // H
        qkv = (lambda x, *d: x.permute(*d))((x @ wqkv).reshape(B, S, 3, H, Dh), 2, 0, 3, 1, 4)
        q, k, v = qkv[0], qkv[1], qkv[2]
        scores = torch.einsum("bhqd,bhkd->bhqk", q, k) * (Dh ** -0.5)
        p = _softmax(scores, axis=-1)
        o = torch.einsum("bhqk,bhkd->bhqd", p, v)
        return (lambda x, *d: x.permute(*d))(o, 0, 2, 1, 3).reshape(B, S, D) @ wo

    def _B_ref(x, w1, b1, w2, b2):
        y = _layernorm(x, axis=-1)
        h = _gelu(torch.einsum("bsd,df->bsf", y, w1) + b1)
        return torch.einsum("bsf,fd->bsd", h, w2) + b2

    x = A_x
    xn = _layernorm(x, axis=-1)
    return x + _A_ref(xn, A_wqkv, A_wo) + _B_ref(xn, B_w1, B_b1, B_w2, B_b2)
```

```cpp
#include <cuda_runtime.h>
#include <cuda_bf16.h>
#include <cuda.h>
#include <stdint.h>

namespace {

constexpr int S_LEN = 2048, DM = 640, NH = 32, FF = 1536, NQKV = 1920;
constexpr float LN_EPS = 1e-5f;

__device__ __align__(1024) __nv_bfloat16 g_qkv[3 * NH * 256 * 192];
__device__ __align__(1024) __nv_bfloat16 g_hid[16 * 24 * 8192];
__device__ __align__(1024) __nv_bfloat16 g_att[16 * 10 * 8192];
__device__ float4 g_rowstat[S_LEN];
__device__ float g_colsum[NQKV + FF];
__device__ float g_knorm[NH * 128];
__device__ float g_vmax[NH * 128];
__device__ unsigned g_statcnt;

__device__ __forceinline__ uint32_t smem_u32(const void* p) { return (uint32_t)__cvta_generic_to_shared(p); }
__device__ __forceinline__ void wg_fence() { asm volatile("wgmma.fence.sync.aligned;" ::: "memory"); }
__device__ __forceinline__ void wg_commit() { asm volatile("wgmma.commit_group.sync.aligned;" ::: "memory"); }
template <int N> __device__ __forceinline__ void wg_wait() { asm volatile("wgmma.wait_group.sync.aligned %0;" ::"n"(N) : "memory"); }
__device__ __forceinline__ void mbar_init(uint32_t bar, int cnt) { asm volatile("mbarrier.init.shared::cta.b64 [%0], %1;" ::"r"(bar), "r"(cnt)); }
__device__ __forceinline__ void mbar_expect(uint32_t bar, uint32_t bytes) {
  asm volatile("mbarrier.arrive.expect_tx.shared::cta.b64 _, [%0], %1;" ::"r"(bar), "r"(bytes) : "memory");
}
__device__ __forceinline__ void mbar_arrive(uint32_t bar) { asm volatile("mbarrier.arrive.shared::cta.b64 _, [%0];" ::"r"(bar) : "memory"); }
__device__ __forceinline__ void mbar_arrive_cta(uint32_t bar, uint32_t cta) {
  asm volatile("{\n.reg .b32 r;\nmapa.shared::cluster.u32 r, %0, %1;\nmbarrier.arrive.shared::cluster.b64 _, [r];\n}" ::"r"(bar), "r"(cta) : "memory");
}
__device__ __forceinline__ void mbar_wait(uint32_t bar, uint32_t parity) {
  asm volatile("{\n.reg .pred p;\nWAIT:\nmbarrier.try_wait.parity.shared::cta.b64 p, [%0], %1;\n@p bra DONE;\nbra WAIT;\nDONE:\n}" ::"r"(bar), "r"(parity) : "memory");
}
__device__ __forceinline__ void bulk_load(uint32_t dst, const void* src, uint32_t bytes, uint32_t bar) {
  asm volatile("cp.async.bulk.shared::cluster.global.mbarrier::complete_tx::bytes [%0], [%1], %2, [%3];" ::"r"(dst), "l"(src), "r"(bytes), "r"(bar) : "memory");
}
__device__ __forceinline__ void bulk_load_mc(uint32_t dst, const void* src, uint32_t bytes, uint32_t bar, uint16_t mask) {
  asm volatile("cp.async.bulk.shared::cluster.global.mbarrier::complete_tx::bytes.multicast::cluster [%0], [%1], %2, [%3], %4;" ::"r"(dst), "l"(src), "r"(bytes), "r"(bar), "h"(mask) : "memory");
}
__device__ __forceinline__ void tma_2d(uint32_t dst, const CUtensorMap* tm, int c0, int c1, uint32_t bar) {
  asm volatile("cp.async.bulk.tensor.2d.shared::cluster.global.mbarrier::complete_tx::bytes [%0], [%1, {%3, %4}], [%2];" ::"r"(dst), "l"(tm), "r"(bar), "r"(c0), "r"(c1) : "memory");
}
__device__ __forceinline__ void tma_2d_mc(uint32_t dst, const CUtensorMap* tm, int c0, int c1, uint32_t bar, uint16_t mask) {
  asm volatile("cp.async.bulk.tensor.2d.shared::cluster.global.mbarrier::complete_tx::bytes.multicast::cluster [%0], [%1, {%3, %4}], [%2], %5;" ::"r"(dst), "l"(tm), "r"(bar), "r"(c0), "r"(c1), "h"(mask) : "memory");
}
__device__ __forceinline__ void tma_3d(uint32_t dst, const CUtensorMap* tm, int c0, int c1, int c2, uint32_t bar) {
  asm volatile("cp.async.bulk.tensor.3d.shared::cluster.global.mbarrier::complete_tx::bytes [%0], [%1, {%3, %4, %5}], [%2];" ::"r"(dst), "l"(tm), "r"(bar), "r"(c0), "r"(c1), "r"(c2) : "memory");
}
__device__ __forceinline__ void cluster_sync() { asm volatile("barrier.cluster.arrive.release.aligned;\nbarrier.cluster.wait.acquire.aligned;" ::: "memory"); }
__device__ __forceinline__ void pdl_wait() { asm volatile("griddepcontrol.wait;" ::: "memory"); }
__device__ __forceinline__ void pdl_launch() { asm volatile("griddepcontrol.launch_dependents;" ::: "memory"); }
__device__ __forceinline__ void bar_sync(int id, int n) { asm volatile("bar.sync %0, %1;" ::"r"(id), "r"(n) : "memory"); }
__device__ __forceinline__ float ex2(float x) { float y; asm("ex2.approx.ftz.f32 %0, %1;" : "=f"(y) : "f"(x)); return y; }
__device__ __forceinline__ float tanh_fast(float x) { float y; asm("tanh.approx.f32 %0, %1;" : "=f"(y) : "f"(x)); return y; }
__device__ __forceinline__ uint32_t pack_bf16(float lo, float hi) { uint32_t r; asm("cvt.rn.bf16x2.f32 %0, %1, %2;" : "=r"(r) : "f"(hi), "f"(lo)); return r; }
__device__ __forceinline__ uint32_t hfma2_bf16(uint32_t a, uint32_t b, uint32_t c) { uint32_t r; asm("fma.rn.bf16x2 %0, %1, %2, %3;" : "=r"(r) : "r"(a), "r"(b), "r"(c)); return r; }
__device__ __forceinline__ uint32_t hmul2_bf16(uint32_t a, uint32_t b) { uint32_t r; asm("mul.rn.bf16x2 %0, %1, %2;" : "=r"(r) : "r"(a), "r"(b)); return r; }
template <int LUT> __device__ __forceinline__ uint32_t lop3(uint32_t a, uint32_t b, uint32_t c) {
  uint32_t r; asm("lop3.b32 %0, %1, %2, %3, %4;" : "=r"(r) : "r"(a), "r"(b), "r"(c), "n"(LUT)); return r;
}
__device__ __forceinline__ float bf_lo(uint32_t v) { return __uint_as_float(v << 16); }
__device__ __forceinline__ float bf_hi(uint32_t v) { return __uint_as_float(v & 0xFFFF0000u); }

__device__ __forceinline__ void wgmma_n240_ss(float (&d)[120], uint32_t alo, uint32_t ahi, uint32_t blo, uint32_t bhi, int scaleD) {
  asm volatile("{\n.reg .pred p;\n.reg .b64 da, db;\nsetp.ne.b32 p, %124, 0;\nmov.b64 da, {%120, %121};\nmov.b64 db, {%122, %123};\n"
    "wgmma.mma_async.sync.aligned.m64n240k16.f32.bf16.bf16 "
    "{%0,%1,%2,%3,%4,%5,%6,%7,%8,%9,%10,%11,%12,%13,%14,%15,%16,%17,%18,%19,%20,%21,%22,%23,%24,%25,%26,%27,%28,%29,%30,%31,%32,%33,%34,%35,%36,%37,%38,%39,%40,%41,%42,%43,%44,%45,%46,%47,%48,%49,%50,%51,%52,%53,%54,%55,%56,%57,%58,%59,%60,%61,%62,%63,%64,%65,%66,%67,%68,%69,%70,%71,%72,%73,%74,%75,%76,%77,%78,%79,%80,%81,%82,%83,%84,%85,%86,%87,%88,%89,%90,%91,%92,%93,%94,%95,%96,%97,%98,%99,%100,%101,%102,%103,%104,%105,%106,%107,%108,%109,%110,%111,%112,%113,%114,%115,%116,%117,%118,%119}, "
    "da, db, p, 1, 1, 0, 1;\n}\n"
    :
      "+f"(d[0]), "+f"(d[1]), "+f"(d[2]), "+f"(d[3]), "+f"(d[4]), "+f"(d[5]), "+f"(d[6]), "+f"(d[7]),
      "+f"(d[8]), "+f"(d[9]), "+f"(d[10]), "+f"(d[11]), "+f"(d[12]), "+f"(d[13]), "+f"(d[14]), "+f"(d[15]),
      "+f"(d[16]), "+f"(d[17]), "+f"(d[18]), "+f"(d[19]), "+f"(d[20]), "+f"(d[21]), "+f"(d[22]), "+f"(d[23]),
      "+f"(d[24]), "+f"(d[25]), "+f"(d[26]), "+f"(d[27]), "+f"(d[28]), "+f"(d[29]), "+f"(d[30]), "+f"(d[31]),
      "+f"(d[32]), "+f"(d[33]), "+f"(d[34]), "+f"(d[35]), "+f"(d[36]), "+f"(d[37]), "+f"(d[38]), "+f"(d[39]),
      "+f"(d[40]), "+f"(d[41]), "+f"(d[42]), "+f"(d[43]), "+f"(d[44]), "+f"(d[45]), "+f"(d[46]), "+f"(d[47]),
      "+f"(d[48]), "+f"(d[49]), "+f"(d[50]), "+f"(d[51]), "+f"(d[52]), "+f"(d[53]), "+f"(d[54]), "+f"(d[55]),
      "+f"(d[56]), "+f"(d[57]), "+f"(d[58]), "+f"(d[59]), "+f"(d[60]), "+f"(d[61]), "+f"(d[62]), "+f"(d[63]),
      "+f"(d[64]), "+f"(d[65]), "+f"(d[66]), "+f"(d[67]), "+f"(d[68]), "+f"(d[69]), "+f"(d[70]), "+f"(d[71]),
      "+f"(d[72]), "+f"(d[73]), "+f"(d[74]), "+f"(d[75]), "+f"(d[76]), "+f"(d[77]), "+f"(d[78]), "+f"(d[79]),
      "+f"(d[80]), "+f"(d[81]), "+f"(d[82]), "+f"(d[83]), "+f"(d[84]), "+f"(d[85]), "+f"(d[86]), "+f"(d[87]),
      "+f"(d[88]), "+f"(d[89]), "+f"(d[90]), "+f"(d[91]), "+f"(d[92]), "+f"(d[93]), "+f"(d[94]), "+f"(d[95]),
      "+f"(d[96]), "+f"(d[97]), "+f"(d[98]), "+f"(d[99]), "+f"(d[100]), "+f"(d[101]), "+f"(d[102]),
      "+f"(d[103]), "+f"(d[104]), "+f"(d[105]), "+f"(d[106]), "+f"(d[107]), "+f"(d[108]), "+f"(d[109]),
      "+f"(d[110]), "+f"(d[111]), "+f"(d[112]), "+f"(d[113]), "+f"(d[114]), "+f"(d[115]), "+f"(d[116]),
      "+f"(d[117]), "+f"(d[118]), "+f"(d[119])
    : "r"(alo), "r"(ahi), "r"(blo), "r"(bhi), "r"(scaleD));
}
__device__ __forceinline__ void wgmma_n192_ss(float (&d)[96], uint32_t alo, uint32_t ahi, uint32_t blo, uint32_t bhi, int scaleD) {
  asm volatile("{\n.reg .pred p;\n.reg .b64 da, db;\nsetp.ne.b32 p, %100, 0;\nmov.b64 da, {%96, %97};\nmov.b64 db, {%98, %99};\n"
    "wgmma.mma_async.sync.aligned.m64n192k16.f32.bf16.bf16 "
    "{%0,%1,%2,%3,%4,%5,%6,%7,%8,%9,%10,%11,%12,%13,%14,%15,%16,%17,%18,%19,%20,%21,%22,%23,%24,%25,%26,%27,%28,%29,%30,%31,%32,%33,%34,%35,%36,%37,%38,%39,%40,%41,%42,%43,%44,%45,%46,%47,%48,%49,%50,%51,%52,%53,%54,%55,%56,%57,%58,%59,%60,%61,%62,%63,%64,%65,%66,%67,%68,%69,%70,%71,%72,%73,%74,%75,%76,%77,%78,%79,%80,%81,%82,%83,%84,%85,%86,%87,%88,%89,%90,%91,%92,%93,%94,%95}, "
    "da, db, p, 1, 1, 0, 1;\n}\n"
    :
      "+f"(d[0]), "+f"(d[1]), "+f"(d[2]), "+f"(d[3]), "+f"(d[4]), "+f"(d[5]), "+f"(d[6]), "+f"(d[7]),
      "+f"(d[8]), "+f"(d[9]), "+f"(d[10]), "+f"(d[11]), "+f"(d[12]), "+f"(d[13]), "+f"(d[14]), "+f"(d[15]),
      "+f"(d[16]), "+f"(d[17]), "+f"(d[18]), "+f"(d[19]), "+f"(d[20]), "+f"(d[21]), "+f"(d[22]), "+f"(d[23]),
      "+f"(d[24]), "+f"(d[25]), "+f"(d[26]), "+f"(d[27]), "+f"(d[28]), "+f"(d[29]), "+f"(d[30]), "+f"(d[31]),
      "+f"(d[32]), "+f"(d[33]), "+f"(d[34]), "+f"(d[35]), "+f"(d[36]), "+f"(d[37]), "+f"(d[38]), "+f"(d[39]),
      "+f"(d[40]), "+f"(d[41]), "+f"(d[42]), "+f"(d[43]), "+f"(d[44]), "+f"(d[45]), "+f"(d[46]), "+f"(d[47]),
      "+f"(d[48]), "+f"(d[49]), "+f"(d[50]), "+f"(d[51]), "+f"(d[52]), "+f"(d[53]), "+f"(d[54]), "+f"(d[55]),
      "+f"(d[56]), "+f"(d[57]), "+f"(d[58]), "+f"(d[59]), "+f"(d[60]), "+f"(d[61]), "+f"(d[62]), "+f"(d[63]),
      "+f"(d[64]), "+f"(d[65]), "+f"(d[66]), "+f"(d[67]), "+f"(d[68]), "+f"(d[69]), "+f"(d[70]), "+f"(d[71]),
      "+f"(d[72]), "+f"(d[73]), "+f"(d[74]), "+f"(d[75]), "+f"(d[76]), "+f"(d[77]), "+f"(d[78]), "+f"(d[79]),
      "+f"(d[80]), "+f"(d[81]), "+f"(d[82]), "+f"(d[83]), "+f"(d[84]), "+f"(d[85]), "+f"(d[86]), "+f"(d[87]),
      "+f"(d[88]), "+f"(d[89]), "+f"(d[90]), "+f"(d[91]), "+f"(d[92]), "+f"(d[93]), "+f"(d[94]), "+f"(d[95])
    : "r"(alo), "r"(ahi), "r"(blo), "r"(bhi), "r"(scaleD));
}
__device__ __forceinline__ void wgmma_n80_ss(float (&d)[40], uint32_t alo, uint32_t ahi, uint32_t blo, uint32_t bhi, int scaleD) {
  asm volatile("{\n.reg .pred p;\n.reg .b64 da, db;\nsetp.ne.b32 p, %44, 0;\nmov.b64 da, {%40, %41};\nmov.b64 db, {%42, %43};\n"
    "wgmma.mma_async.sync.aligned.m64n80k16.f32.bf16.bf16 "
    "{%0,%1,%2,%3,%4,%5,%6,%7,%8,%9,%10,%11,%12,%13,%14,%15,%16,%17,%18,%19,%20,%21,%22,%23,%24,%25,%26,%27,%28,%29,%30,%31,%32,%33,%34,%35,%36,%37,%38,%39}, "
    "da, db, p, 1, 1, 0, 1;\n}\n"
    :
      "+f"(d[0]), "+f"(d[1]), "+f"(d[2]), "+f"(d[3]), "+f"(d[4]), "+f"(d[5]), "+f"(d[6]), "+f"(d[7]),
      "+f"(d[8]), "+f"(d[9]), "+f"(d[10]), "+f"(d[11]), "+f"(d[12]), "+f"(d[13]), "+f"(d[14]), "+f"(d[15]),
      "+f"(d[16]), "+f"(d[17]), "+f"(d[18]), "+f"(d[19]), "+f"(d[20]), "+f"(d[21]), "+f"(d[22]), "+f"(d[23]),
      "+f"(d[24]), "+f"(d[25]), "+f"(d[26]), "+f"(d[27]), "+f"(d[28]), "+f"(d[29]), "+f"(d[30]), "+f"(d[31]),
      "+f"(d[32]), "+f"(d[33]), "+f"(d[34]), "+f"(d[35]), "+f"(d[36]), "+f"(d[37]), "+f"(d[38]), "+f"(d[39])
    : "r"(alo), "r"(ahi), "r"(blo), "r"(bhi), "r"(scaleD));
}
__device__ __forceinline__ void wgmma_n64_rs(float (&d)[32], uint32_t a0, uint32_t a1, uint32_t a2, uint32_t a3, uint32_t blo, uint32_t bhi, int scaleD) {
  asm volatile("{\n.reg .pred p;\n.reg .b64 db;\nsetp.ne.b32 p, %38, 0;\nmov.b64 db, {%36, %37};\n"
    "wgmma.mma_async.sync.aligned.m64n64k16.f32.bf16.bf16 "
    "{%0,%1,%2,%3,%4,%5,%6,%7,%8,%9,%10,%11,%12,%13,%14,%15,%16,%17,%18,%19,%20,%21,%22,%23,%24,%25,%26,%27,%28,%29,%30,%31}, "
    "{%32, %33, %34, %35}, db, p, 1, 1, 0;\n}\n"
    :
      "+f"(d[0]), "+f"(d[1]), "+f"(d[2]), "+f"(d[3]), "+f"(d[4]), "+f"(d[5]), "+f"(d[6]), "+f"(d[7]),
      "+f"(d[8]), "+f"(d[9]), "+f"(d[10]), "+f"(d[11]), "+f"(d[12]), "+f"(d[13]), "+f"(d[14]), "+f"(d[15]),
      "+f"(d[16]), "+f"(d[17]), "+f"(d[18]), "+f"(d[19]), "+f"(d[20]), "+f"(d[21]), "+f"(d[22]), "+f"(d[23]),
      "+f"(d[24]), "+f"(d[25]), "+f"(d[26]), "+f"(d[27]), "+f"(d[28]), "+f"(d[29]), "+f"(d[30]), "+f"(d[31])
    : "r"(a0), "r"(a1), "r"(a2), "r"(a3), "r"(blo), "r"(bhi), "r"(scaleD));
}
__device__ __forceinline__ void wgmma_n24_rs(float (&d)[12], uint32_t a0, uint32_t a1, uint32_t a2, uint32_t a3, uint32_t blo, uint32_t bhi, int scaleD) {
  asm volatile("{\n.reg .pred p;\n.reg .b64 db;\nsetp.ne.b32 p, %18, 0;\nmov.b64 db, {%16, %17};\n"
    "wgmma.mma_async.sync.aligned.m64n24k16.f32.bf16.bf16 "
    "{%0,%1,%2,%3,%4,%5,%6,%7,%8,%9,%10,%11}, "
    "{%12, %13, %14, %15}, db, p, 1, 1, 1;\n}\n"
    :
      "+f"(d[0]), "+f"(d[1]), "+f"(d[2]), "+f"(d[3]), "+f"(d[4]), "+f"(d[5]), "+f"(d[6]), "+f"(d[7]),
      "+f"(d[8]), "+f"(d[9]), "+f"(d[10]), "+f"(d[11])
    : "r"(a0), "r"(a1), "r"(a2), "r"(a3), "r"(blo), "r"(bhi), "r"(scaleD));
}

constexpr uint32_t MUFU_MASK = 0x4949;
constexpr float QSCALE = 0.22360679774997896f * 1.4426950408889634f;

constexpr int K1_STAGES = 4, K1_STAGE = 16384 + 32768;
constexpr int K1_PARAM = K1_STAGES * K1_STAGE;
constexpr int K1_BARS = K1_PARAM + 4608;
constexpr int K1_RED = K1_BARS + 128;
constexpr int K1_SMEM = K1_RED + 512;

__global__ void __launch_bounds__(384, 1)
k1_proj(const __grid_constant__ CUtensorMap tmX, const __grid_constant__ CUtensorMap tmWqkv, const __grid_constant__ CUtensorMap tmW1,
        const __nv_bfloat16* __restrict__ x, const __nv_bfloat16* __restrict__ wqkv, const __nv_bfloat16* __restrict__ w1,
        const __nv_bfloat16* __restrict__ b1) {
  extern __shared__ __align__(1024) uint8_t smem[];
  const uint32_t sb = smem_u32(smem);
  const uint32_t sd = sb & 0x3FFFF;
  const uint32_t full = sb + K1_BARS, empty = full + 32, pready = full + 64;
  float* s_cs = reinterpret_cast<float*>(smem + K1_PARAM);
  float* s_cs1 = s_cs + 240;
  float* s_b1h = s_cs1 + 192;
  float4* s_row = reinterpret_cast<float4*>(smem + K1_PARAM + 2560);
  const int tid = threadIdx.x, warp = tid >> 5, lane = tid & 31;
  const int rank = blockIdx.x & 1;
  const int cb = (blockIdx.x >> 1) & 7, rb = ((blockIdx.x >> 4) << 1) | rank;

  if (tid == 0) {
    for (int s = 0; s < K1_STAGES; s++) { mbar_init(full + 8 * s, 1); mbar_init(empty + 8 * s, 16); }
    mbar_init(pready, 96);
    asm volatile("fence.mbarrier_init.release.cluster;" ::: "memory");
  }
  __syncthreads();
  cluster_sync();
  pdl_launch();

  if (warp >= 8) {
    if (warp == 8) {
      if (lane == 0) {
        int s = 0; uint32_t ph = 1;
        for (int tile = 0; tile < 2; tile++) {
          const CUtensorMap* tw = tile ? &tmW1 : &tmWqkv;
          const int nbox = tile ? 3 : 4, col0 = cb * (tile ? 192 : 240);
          for (int kb = 0; kb < 10; kb++) {
            mbar_wait(empty + 8 * s, ph);
            const uint32_t sa = sb + s * K1_STAGE, sbb = sa + 16384;
            mbar_expect(full + 8 * s, 16384 + nbox * 8192);
            tma_2d(sa, &tmX, kb * 64, rb * 128, full + 8 * s);
            for (int b = 0; b < nbox; b++)
              tma_2d_mc(sbb + b * 8192 + rank * 4096, tw, col0 + b * 64, kb * 64 + rank * 32, full + 8 * s, 3);
            if (++s == K1_STAGES) { s = 0; ph ^= 1; }
          }
        }
      }
    } else {
      const int w = warp - 9;
      for (int rr = w; rr < 16; rr += 3) {
        const int row = blockIdx.x * 16 + rr;
        const uint2* px = reinterpret_cast<const uint2*>(x + (size_t)row * DM);
        float v[20]; float sum = 0.f;
        #pragma unroll
        for (int i = 0; i < 5; i++) {
          const uint2 u = __ldg(px + i * 32 + lane);
          v[4 * i] = bf_lo(u.x); v[4 * i + 1] = bf_hi(u.x); v[4 * i + 2] = bf_lo(u.y); v[4 * i + 3] = bf_hi(u.y);
          sum += (v[4 * i] + v[4 * i + 1]) + (v[4 * i + 2] + v[4 * i + 3]);
        }
        #pragma unroll
        for (int o = 16; o; o >>= 1) sum += __shfl_xor_sync(~0u, sum, o);
        const float mean = sum * (1.f / DM);
        float sq = 0.f;
        #pragma unroll
        for (int i = 0; i < 20; i++) { const float d = v[i] - mean; sq = fmaf(d, d, sq); }
        #pragma unroll
        for (int o = 16; o; o >>= 1) sq += __shfl_xor_sync(~0u, sq, o);
        const float var = sq * (1.f / DM);
        const float r1 = 1.f / sqrtf(var + LN_EPS);
        const float r2 = 1.f / sqrtf(var * r1 * r1 + LN_EPS);
        if (lane == 0) g_rowstat[row] = make_float4(mean, r1, r1 * r2, 0.f);
      }
      float* s_red = reinterpret_cast<float*>(smem + K1_RED);
      if (blockIdx.x < 108) {
        const int grp = blockIdx.x * 4 + (lane & 3);
        const bool is1 = grp >= 240;
        const __nv_bfloat16* wp = is1 ? w1 + (grp - 240) * 8 : wqkv + grp * 8;
        const int ld = is1 ? FF : NQKV;
        float a[8];
        #pragma unroll
        for (int i = 0; i < 8; i++) a[i] = 0.f;
        #pragma unroll 9
        for (int k = w * 8 + (lane >> 2); k < DM; k += 24) {
          const uint4 u = __ldg(reinterpret_cast<const uint4*>(wp + (size_t)k * ld));
          a[0] += bf_lo(u.x); a[1] += bf_hi(u.x); a[2] += bf_lo(u.y); a[3] += bf_hi(u.y);
          a[4] += bf_lo(u.z); a[5] += bf_hi(u.z); a[6] += bf_lo(u.w); a[7] += bf_hi(u.w);
        }
        #pragma unroll
        for (int i = 0; i < 8; i++) {
          a[i] += __shfl_xor_sync(~0u, a[i], 4); a[i] += __shfl_xor_sync(~0u, a[i], 8); a[i] += __shfl_xor_sync(~0u, a[i], 16);
        }
        if (lane < 4) {
          #pragma unroll
          for (int i = 0; i < 8; i++) s_red[w * 32 + lane * 8 + i] = a[i];
        }
        bar_sync(2, 96);
        if (w == 0) g_colsum[blockIdx.x * 32 + lane] = s_red[lane] + s_red[32 + lane] + s_red[64 + lane];
      }
      __threadfence();
      bar_sync(2, 96);
      if (w == 0 && lane == 0) {
        const unsigned old = atomicAdd(&g_statcnt, 1u);
        const unsigned target = (old & ~127u) + 128u;
        unsigned cur; int spins = 0;
        do { asm volatile("ld.acquire.gpu.global.u32 %0, [%1];" : "=r"(cur) : "l"(&g_statcnt) : "memory"); } while ((int)(cur - target) < 0 && ++spins < (1 << 22));
      }
      bar_sync(2, 96);
      const int t96 = tid - 288;
      for (int i = t96; i < 240; i += 96) s_cs[i] = __ldcg(&g_colsum[cb * 240 + i]);
      for (int i = t96; i < 192; i += 96) { s_cs1[i] = __ldcg(&g_colsum[NQKV + cb * 192 + i]); s_b1h[i] = 0.5f * __bfloat162float(b1[cb * 192 + i]); }
      for (int i = t96; i < 128; i += 96) s_row[i] = __ldcg(&g_rowstat[rb * 128 + i]);
      mbar_arrive(pready);
    }
  } else {
    const int wg = warp >> 2, w4 = warp & 3, g = lane >> 2, t = lane & 3;
    int s = 0; uint32_t ph = 0;
    const int tg0 = rb * 16 + wg * 8 + w4 * 2;
    {
      float acc[120];
      for (int kb = 0; kb < 10; kb++) {
        mbar_wait(full + 8 * s, ph);
        const uint32_t alo = ((sd + s * K1_STAGE + wg * 8192) >> 4) | (1u << 16);
        const uint32_t blo = ((sd + s * K1_STAGE + 16384) >> 4) | (512u << 16);
        wg_fence();
        #pragma unroll
        for (int k = 0; k < 4; k++) wgmma_n240_ss(acc, alo + k * 2, 64u | (1u << 30), blo + k * 128, 64u | (1u << 30), (kb | k) != 0);
        wg_commit();
        if (kb > 0) { wg_wait<1>(); const int sp = (s + K1_STAGES - 1) % K1_STAGES; if (lane < 2) mbar_arrive_cta(empty + 8 * sp, lane); }
        if (++s == K1_STAGES) { s = 0; ph ^= 1; }
      }
      wg_wait<0>();
      { const int sp = (s + K1_STAGES - 1) % K1_STAGES; if (lane < 2) mbar_arrive_cta(empty + 8 * sp, lane); }
      mbar_wait(pready, 0);
      const float4 st0 = s_row[wg * 64 + w4 * 16 + g], st1 = s_row[wg * 64 + w4 * 16 + g + 8];
      const float nm0 = -st0.x, nm1 = -st1.x;
      #pragma unroll
      for (int pi = 0; pi < 6; pi++) {
        const int P = cb * 6 + pi, sec = P >> 4, he = (P & 15) * 2;
        const float sc = sec == 0 ? QSCALE : 1.f;
        const float r0 = st0.y * sc, r1 = st1.y * sc;
        uint32_t* de = reinterpret_cast<uint32_t*>(g_qkv + ((size_t)(sec * NH + he) * 256 + tg0) * 192) + lane;
        uint32_t* dod = de + 256 * 96;
        float v[5][4];
        #pragma unroll
        for (int gi = 0; gi < 5; gi++) {
          const int i = pi * 5 + gi;
          const float2 cs = *reinterpret_cast<const float2*>(s_cs + 8 * i + 2 * t);
          v[gi][0] = fmaf(nm0, cs.x, acc[4 * i]) * r0;     v[gi][1] = fmaf(nm0, cs.y, acc[4 * i + 1]) * r0;
          v[gi][2] = fmaf(nm1, cs.x, acc[4 * i + 2]) * r1; v[gi][3] = fmaf(nm1, cs.y, acc[4 * i + 3]) * r1;
        }
        uint32_t aug0, aug1;
        if (sec == 0) { aug0 = aug1 = 0x3F803F80u; }
        else if (sec == 2) { aug0 = aug1 = 0x00003F80u; }
        else {
          aug0 = ((MUFU_MASK >> (tg0 & 15)) & 1) ? 0u : 0x3B8043C0u;
          aug1 = ((MUFU_MASK >> ((tg0 + 1) & 15)) & 1) ? 0u : 0x3B8043C0u;
        }
        const uint32_t w20 = pack_bf16(v[2][0], v[2][1]), w21 = pack_bf16(v[2][2], v[2][3]);
        de[0] = pack_bf16(v[0][0], v[0][1]);       de[96] = pack_bf16(v[0][2], v[0][3]);
        de[32] = pack_bf16(v[1][0], v[1][1]);      de[96 + 32] = pack_bf16(v[1][2], v[1][3]);
        de[64] = t < 2 ? w20 : (t == 2 ? aug0 : 0u); de[96 + 64] = t < 2 ? w21 : (t == 2 ? aug1 : 0u);
        dod[0] = pack_bf16(v[3][0], v[3][1]);      dod[96] = pack_bf16(v[3][2], v[3][3]);
        dod[32] = pack_bf16(v[4][0], v[4][1]);     dod[96 + 32] = pack_bf16(v[4][2], v[4][3]);
        dod[64] = t >= 2 ? w20 : (t == 0 ? aug0 : 0u); dod[96 + 64] = t >= 2 ? w21 : (t == 0 ? aug1 : 0u);
        if (sec == 1) {
          float e0 = 0.f, e1 = 0.f, o0 = 0.f, o1 = 0.f;
          #pragma unroll
          for (int gi = 0; gi < 2; gi++) { e0 = fmaf(v[gi][0], v[gi][0], fmaf(v[gi][1], v[gi][1], e0)); e1 = fmaf(v[gi][2], v[gi][2], fmaf(v[gi][3], v[gi][3], e1)); }
          #pragma unroll
          for (int gi = 3; gi < 5; gi++) { o0 = fmaf(v[gi][0], v[gi][0], fmaf(v[gi][1], v[gi][1], o0)); o1 = fmaf(v[gi][2], v[gi][2], fmaf(v[gi][3], v[gi][3], o1)); }
          const float m0 = fmaf(v[2][0], v[2][0], v[2][1] * v[2][1]), m1 = fmaf(v[2][2], v[2][2], v[2][3] * v[2][3]);
          if (t < 2) { e0 += m0; e1 += m1; } else { o0 += m0; o1 += m1; }
          #pragma unroll
          for (int o = 1; o < 4; o <<= 1) {
            e0 += __shfl_xor_sync(~0u, e0, o); e1 += __shfl_xor_sync(~0u, e1, o); o0 += __shfl_xor_sync(~0u, o0, o); o1 += __shfl_xor_sync(~0u, o1, o);
          }
          const unsigned me = __reduce_max_sync(~0u, max(__float_as_uint(e0), __float_as_uint(e1)));
          const unsigned mo = __reduce_max_sync(~0u, max(__float_as_uint(o0), __float_as_uint(o1)));
          if (lane == 0) { g_knorm[he * 128 + (tg0 >> 1)] = __uint_as_float(me); g_knorm[(he + 1) * 128 + (tg0 >> 1)] = __uint_as_float(mo); }
        } else if (sec == 2) {
          unsigned m = 0;
          #pragma unroll
          for (int gi = 0; gi < 5; gi++)
            #pragma unroll
            for (int e = 0; e < 4; e++) m = max(m, __float_as_uint(v[gi][e]) & 0x7FFFFFFFu);
          m = __reduce_max_sync(~0u, m);
          if (lane == 0) { g_vmax[he * 128 + (tg0 >> 1)] = __uint_as_float(m); g_vmax[(he + 1) * 128 + (tg0 >> 1)] = __uint_as_float(m); }
        }
      }
    }
    {
      float acc[96];
      for (int kb = 0; kb < 10; kb++) {
        mbar_wait(full + 8 * s, ph);
        const uint32_t alo = ((sd + s * K1_STAGE + wg * 8192) >> 4) | (1u << 16);
        const uint32_t blo = ((sd + s * K1_STAGE + 16384) >> 4) | (512u << 16);
        wg_fence();
        #pragma unroll
        for (int k = 0; k < 4; k++) wgmma_n192_ss(acc, alo + k * 2, 64u | (1u << 30), blo + k * 128, 64u | (1u << 30), (kb | k) != 0);
        wg_commit();
        if (kb > 0) { wg_wait<1>(); const int sp = (s + K1_STAGES - 1) % K1_STAGES; if (lane < 2) mbar_arrive_cta(empty + 8 * sp, lane); }
        if (++s == K1_STAGES) { s = 0; ph ^= 1; }
      }
      wg_wait<0>();
      const float4 st0 = s_row[wg * 64 + w4 * 16 + g], st1 = s_row[wg * 64 + w4 * 16 + g + 8];
      const float nm0 = -st0.x, nm1 = -st1.x, a0 = 0.5f * st0.z, a1 = 0.5f * st1.z;
      uint32_t* dst = reinterpret_cast<uint32_t*>(g_hid + ((size_t)(rb * 24 + cb * 3) * 16 + wg * 8 + w4 * 2) * 512) + lane;
      constexpr float GA = 1.5957691216057308f, GB = 1.5957691216057308f * 0.044715f * 4.f;
      #pragma unroll
      for (int i = 0; i < 24; i++) {
        const float2 cs = *reinterpret_cast<const float2*>(s_cs1 + 8 * i + 2 * t);
        const float2 bb = *reinterpret_cast<const float2*>(s_b1h + 8 * i + 2 * t);
        float h[4];
        h[0] = fmaf(fmaf(nm0, cs.x, acc[4 * i]), a0, bb.x);     h[1] = fmaf(fmaf(nm0, cs.y, acc[4 * i + 1]), a0, bb.y);
        h[2] = fmaf(fmaf(nm1, cs.x, acc[4 * i + 2]), a1, bb.x); h[3] = fmaf(fmaf(nm1, cs.y, acc[4 * i + 3]), a1, bb.y);
        #pragma unroll
        for (int e = 0; e < 4; e++) {
          const float u = h[e] * fmaf(h[e] * h[e], GB, GA);
          h[e] = fmaf(h[e], tanh_fast(u), h[e]);
        }
        uint32_t* d = dst + (i >> 3) * 4096 + (i & 7) * 32;
        d[0] = pack_bf16(h[0], h[1]);
        d[256] = pack_bf16(h[2], h[3]);
      }
    }
  }
  __syncthreads();
  cluster_sync();
}

constexpr int KV_TILE = 12288;
constexpr int K2_BARS = 16 * KV_TILE;
constexpr int K2_RED = K2_BARS + 128;
constexpr int K2_SMEM = K2_RED + 128;
constexpr float FAST_BOUND2 = 3600.f;
constexpr float FAST_VMAX = 1.0e15f;

__device__ __forceinline__ uint32_t exp2_pair(float ta, float tb, uint32_t one2) {
  const uint32_t v = __byte_perm(__float_as_uint(ta), __float_as_uint(tb), 0x6521);
  const uint32_t m = lop3<0xEA>(v, 0x007F007Fu, one2);
  const uint32_t q = hfma2_bf16(m, 0xBDF4BDF4u, 0x3EB43EB4u);
  const uint32_t p = hfma2_bf16(q, m, 0xBF3BBF3Bu);
  return hmul2_bf16(v, p);
}
__device__ __forceinline__ void exp_tile(const float (&s)[32], uint32_t (&p)[16], const uint32_t mask, uint32_t one2) {
  #pragma unroll
  for (int i = 0; i < 8; i++) {
    if ((mask >> i) & 1) {
      p[2 * i] = pack_bf16(ex2(s[4 * i]), ex2(s[4 * i + 1]));
      p[2 * i + 1] = pack_bf16(ex2(s[4 * i + 2]), ex2(s[4 * i + 3]));
    } else {
      p[2 * i] = exp2_pair(s[4 * i], s[4 * i + 1], one2);
      p[2 * i + 1] = exp2_pair(s[4 * i + 2], s[4 * i + 3], one2);
    }
  }
}
__device__ __forceinline__ void issue_qk(float (&s)[32], const uint32_t (&qa)[8], uint32_t klo) {
  wgmma_n64_rs(s, qa[0], qa[1], qa[2], qa[3], klo | (8u << 16), 24u, 0);
  wgmma_n64_rs(s, qa[4], qa[5], qa[6], qa[7], klo + 16u, 24u, 1);
}
__device__ __forceinline__ void issue_pv(float (&o)[12], const uint32_t (&p)[16], uint32_t vlo) {
  #pragma unroll
  for (int kk = 0; kk < 4; kk++) wgmma_n24_rs(o, p[4 * kk], p[4 * kk + 1], p[4 * kk + 2], p[4 * kk + 3], vlo + kk * 48u, 8u, 1);
}

__global__ void __launch_bounds__(512, 1) k2_attn() {
  extern __shared__ __align__(1024) uint8_t smem[];
  const uint32_t sb = smem_u32(smem);
  const uint32_t bb = sb + K2_BARS;
  const int h = blockIdx.x >> 2, qq = blockIdx.x & 3;
  const int tid = threadIdx.x, wg = tid >> 7, w4 = (tid >> 5) & 3, lane = tid & 31, t = lane & 3;
  if (tid == 0) {
    for (int j = 0; j < 16; j++) mbar_init(bb + j * 8, 1);
    asm volatile("fence.mbarrier_init.release.cluster;" ::: "memory");
  }
  pdl_wait();
  if (tid == 0) {
    const uint8_t* ksrc = reinterpret_cast<const uint8_t*>(g_qkv + (size_t)(NH + h) * 256 * 192);
    const uint8_t* vsrc = reinterpret_cast<const uint8_t*>(g_qkv + (size_t)(2 * NH + h) * 256 * 192);
    for (int j = 0; j < 16; j++) {
      mbar_expect(bb + j * 8, KV_TILE);
      bulk_load(sb + j * KV_TILE, ksrc + j * 6144, 6144, bb + j * 8);
      bulk_load(sb + j * KV_TILE + 6144, vsrc + j * 6144, 6144, bb + j * 8);
    }
  }
  pdl_launch();
  float kmax2, vmax;
  {
    unsigned a = __float_as_uint(__ldcg(&g_knorm[h * 128 + (tid & 127)])), b = __float_as_uint(__ldcg(&g_vmax[h * 128 + (tid & 127)]));
    a = __reduce_max_sync(~0u, a); b = __reduce_max_sync(~0u, b);
    unsigned* red = reinterpret_cast<unsigned*>(smem + K2_RED);
    if (wg == 0 && lane == 0) { red[w4] = a; red[4 + w4] = b; }
    __syncthreads();
    kmax2 = __uint_as_float(max(max(red[0], red[1]), max(red[2], red[3])));
    vmax = __uint_as_float(max(max(red[4], red[5]), max(red[6], red[7])));
  }
  const bool odd = h & 1;
  const uint32_t kv0 = (sb & 0x3FFFF) >> 4;
  constexpr uint32_t TB = KV_TILE >> 4, VOFF = (6144 >> 4) + (24u << 16);
  uint32_t one2 = 0x3F803F80u;
  asm volatile("" : "+r"(one2));
  #pragma unroll 1
  for (int r = 0; r < 2; r++) {
    const int tg = qq * 64 + wg * 16 + r * 8 + w4 * 2;
    const uint32_t* qp = reinterpret_cast<const uint32_t*>(g_qkv + ((size_t)h * 256 + tg) * 192) + lane;
    uint32_t qa[8];
    qa[0] = __ldcg(qp); qa[1] = __ldcg(qp + 96); qa[2] = __ldcg(qp + 32); qa[3] = __ldcg(qp + 96 + 32);
    qa[4] = __ldcg(qp + 64); qa[5] = __ldcg(qp + 96 + 64); qa[6] = 0; qa[7] = 0;
    const bool real2 = odd ? (t >= 2) : (t < 2);
    float n0 = bf_lo(qa[0]) * bf_lo(qa[0]) + bf_hi(qa[0]) * bf_hi(qa[0]) + bf_lo(qa[2]) * bf_lo(qa[2]) + bf_hi(qa[2]) * bf_hi(qa[2]);
    float n1 = bf_lo(qa[1]) * bf_lo(qa[1]) + bf_hi(qa[1]) * bf_hi(qa[1]) + bf_lo(qa[3]) * bf_lo(qa[3]) + bf_hi(qa[3]) * bf_hi(qa[3]);
    if (real2) { n0 += bf_lo(qa[4]) * bf_lo(qa[4]) + bf_hi(qa[4]) * bf_hi(qa[4]); n1 += bf_lo(qa[5]) * bf_lo(qa[5]) + bf_hi(qa[5]) * bf_hi(qa[5]); }
    n0 += __shfl_xor_sync(~0u, n0, 1); n0 += __shfl_xor_sync(~0u, n0, 2);
    n1 += __shfl_xor_sync(~0u, n1, 1); n1 += __shfl_xor_sync(~0u, n1, 2);
    const bool ok = (n0 * kmax2 * 1.02f <= FAST_BOUND2) && (n1 * kmax2 * 1.02f <= FAST_BOUND2) && (vmax <= FAST_VMAX);
    int allok;
    asm volatile("{\n.reg .pred p, q;\nsetp.ne.b32 p, %1, 0;\nbarrier.red.and.pred q, %2, 128, p;\nselp.b32 %0, 1, 0, q;\n}" : "=r"(allok) : "r"((int)ok), "r"(1 + wg) : "memory");
    float o[12];
    #pragma unroll
    for (int i = 0; i < 12; i++) o[i] = 0.f;
    if (allok) {
      float s0[32], s1[32]; uint32_t p[16];
      if (r == 0) mbar_wait(bb, 0);
      wg_fence(); issue_qk(s0, qa, kv0); wg_commit(); wg_wait<0>();
      #pragma unroll 1
      for (int j = 0; j < 16; j++) {
        const uint32_t base = kv0 + j * TB;
        const int jn = (j + 1) & 15;
        wg_fence(); issue_qk(s1, qa, base + 192u); wg_commit();
        exp_tile(s0, p, MUFU_MASK & 0xFF, one2);
        wg_fence(); issue_pv(o, p, base + VOFF); wg_commit();
        if (r == 0 && j < 15) mbar_wait(bb + jn * 8, 0);
        wg_wait<0>();
        wg_fence(); issue_qk(s0, qa, kv0 + jn * TB); wg_commit();
        exp_tile(s1, p, MUFU_MASK >> 8, one2);
        wg_fence(); issue_pv(o, p, base + VOFF + 4 * 48u); wg_commit();
        wg_wait<0>();
      }
    } else {
      const bool aug = !real2;
      if (aug) { qa[4] = 0; qa[5] = 0; }
      float m0 = -INFINITY, m1 = -INFINITY;
      float s[32]; uint32_t p[16];
      #pragma unroll 1
      for (int u = 0; u < 32; u++) {
        const uint32_t base = kv0 + (u >> 1) * TB;
        mbar_wait(bb + (u >> 1) * 8, 0);
        wg_fence(); issue_qk(s, qa, base + (u & 1) * 192u); wg_commit(); wg_wait<0>();
        float x0 = m0, x1 = m1;
        #pragma unroll
        for (int i = 0; i < 8; i++) { x0 = fmaxf(x0, fmaxf(s[4 * i], s[4 * i + 1])); x1 = fmaxf(x1, fmaxf(s[4 * i + 2], s[4 * i + 3])); }
        x0 = fmaxf(x0, __shfl_xor_sync(~0u, x0, 1)); x0 = fmaxf(x0, __shfl_xor_sync(~0u, x0, 2));
        x1 = fmaxf(x1, __shfl_xor_sync(~0u, x1, 1)); x1 = fmaxf(x1, __shfl_xor_sync(~0u, x1, 2));
        const float c0 = ex2(m0 - x0), c1 = ex2(m1 - x1);
        m0 = x0; m1 = x1;
        #pragma unroll
        for (int i = 0; i < 3; i++) { o[4 * i] *= c0; o[4 * i + 1] *= c0; o[4 * i + 2] *= c1; o[4 * i + 3] *= c1; }
        #pragma unroll
        for (int i = 0; i < 8; i++) {
          p[2 * i] = pack_bf16(ex2(s[4 * i] - m0), ex2(s[4 * i + 1] - m0));
          p[2 * i + 1] = pack_bf16(ex2(s[4 * i + 2] - m1), ex2(s[4 * i + 3] - m1));
        }
        wg_fence(); issue_pv(o, p, base + VOFF + (u & 1) * 4 * 48u); wg_commit(); wg_wait<0>();
      }
    }
    const int src = (lane & ~3) | (odd ? 0 : 2);
    const float i0 = 1.f / __shfl_sync(~0u, o[8], src), i1 = 1.f / __shfl_sync(~0u, o[10], src);
    const int kg0 = (20 * h) >> 3;
    uint32_t* ob = reinterpret_cast<uint32_t*>(g_att + ((size_t)(tg >> 4) * 10 * 16 + (tg & 15)) * 512) + lane;
    auto kaddr = [&](int kg) { return ob + (kg >> 3) * 4096 + (kg & 7) * 32; };
    uint32_t* d0 = kaddr(odd ? kg0 + 1 : kg0);
    uint32_t* d1 = kaddr(odd ? kg0 + 2 : kg0 + 1);
    uint32_t* d2 = kaddr(odd ? kg0 : kg0 + 2);
    d0[0] = pack_bf16(o[0] * i0, o[1] * i0); d0[256] = pack_bf16(o[2] * i1, o[3] * i1);
    d1[0] = pack_bf16(o[4] * i0, o[5] * i0); d1[256] = pack_bf16(o[6] * i1, o[7] * i1);
    if (real2) { d2[0] = pack_bf16(o[8] * i0, o[9] * i0); d2[256] = pack_bf16(o[10] * i1, o[11] * i1); }
  }
}

constexpr int K3_STAGES = 8, K3_STAGE = 16384 + 10240;
constexpr int K3_BARS = K3_STAGES * K3_STAGE;
constexpr int K3_SMEM = K3_BARS + 128;

__global__ void __launch_bounds__(288, 1)
k3_out(const __grid_constant__ CUtensorMap tmW2, const __grid_constant__ CUtensorMap tmWo,
       const __nv_bfloat16* __restrict__ x, const __nv_bfloat16* __restrict__ b2, __nv_bfloat16* __restrict__ out) {
  extern __shared__ __align__(1024) uint8_t smem[];
  const uint32_t sb = smem_u32(smem);
  const uint32_t sd = sb & 0x3FFFF;
  const uint32_t full = sb + K3_BARS, empty = full + 64;
  const int tid = threadIdx.x, warp = tid >> 5, lane = tid & 31;
  const int rank = blockIdx.x & 1;
  const int rb = blockIdx.x >> 3, cb = blockIdx.x & 7;
  if (tid == 0) {
    for (int s = 0; s < K3_STAGES; s++) { mbar_init(full + 8 * s, 1); mbar_init(empty + 8 * s, 16); }
    asm volatile("fence.mbarrier_init.release.cluster;" ::: "memory");
  }
  __syncthreads();
  cluster_sync();
  if (warp == 8) {
    if (lane == 0) {
      int s = 0; uint32_t ph = 1;
      for (int kb = 0; kb < 34; kb++) {
        if (kb == 24) pdl_wait();
        mbar_wait(empty + 8 * s, ph);
        const uint32_t sa = sb + s * K3_STAGE;
        mbar_expect(full + 8 * s, K3_STAGE);
        const __nv_bfloat16* asrc = kb < 24 ? g_hid + (size_t)(rb * 24 + kb) * 8192 : g_att + (size_t)(rb * 10 + kb - 24) * 8192;
        bulk_load_mc(sa + rank * 8192, asrc + rank * 4096, 8192, full + 8 * s, 3);
        if (kb < 24) tma_3d(sa + 16384, &tmW2, 0, kb * 64, cb * 5, full + 8 * s);
        else tma_3d(sa + 16384, &tmWo, 0, (kb - 24) * 64, cb * 5, full + 8 * s);
        if (++s == K3_STAGES) { s = 0; ph ^= 1; }
      }
    }
  } else {
    const int wg = warp >> 2, w4 = warp & 3, g = lane >> 2, t = lane & 3;
    float acc[40];
    int s = 0; uint32_t ph = 0;
    for (int kb = 0; kb < 34; kb++) {
      mbar_wait(full + 8 * s, ph);
      const uint32_t alo = ((sd + s * K3_STAGE + wg * 8192) >> 4) | (8u << 16);
      const uint32_t blo = ((sd + s * K3_STAGE + 16384) >> 4) | (128u << 16);
      wg_fence();
      #pragma unroll
      for (int k = 0; k < 4; k++) wgmma_n80_ss(acc, alo + k * 16, 64u, blo + k * 32, 16u | (3u << 30), (kb | k) != 0);
      wg_commit();
      if (kb > 0) { wg_wait<1>(); const int sp = (s + K3_STAGES - 1) % K3_STAGES; if (lane < 2) mbar_arrive_cta(empty + 8 * sp, lane); }
      if (++s == K3_STAGES) { s = 0; ph ^= 1; }
    }
    wg_wait<0>();
    const int row0 = rb * 128 + wg * 64 + w4 * 16 + g;
    #pragma unroll
    for (int i = 0; i < 10; i++) {
      const int col = cb * 80 + 8 * i + 2 * t;
      const uint32_t bb = *reinterpret_cast<const uint32_t*>(b2 + col);
      const uint32_t x0 = *reinterpret_cast<const uint32_t*>(x + (size_t)row0 * DM + col);
      const uint32_t x1 = *reinterpret_cast<const uint32_t*>(x + (size_t)(row0 + 8) * DM + col);
      *reinterpret_cast<uint32_t*>(out + (size_t)row0 * DM + col) = pack_bf16(acc[4 * i] + bf_lo(bb) + bf_lo(x0), acc[4 * i + 1] + bf_hi(bb) + bf_hi(x0));
      *reinterpret_cast<uint32_t*>(out + (size_t)(row0 + 8) * DM + col) = pack_bf16(acc[4 * i + 2] + bf_lo(bb) + bf_lo(x1), acc[4 * i + 3] + bf_hi(bb) + bf_hi(x1));
    }
  }
  __syncthreads();
  cluster_sync();
}

typedef CUresult (*EncodeTiledFn)(CUtensorMap*, CUtensorMapDataType, cuuint32_t, void*, const cuuint64_t*, const cuuint64_t*, const cuuint32_t*,
                                  const cuuint32_t*, CUtensorMapInterleave, CUtensorMapSwizzle, CUtensorMapL2promotion, CUtensorMapFloatOOBfill);

CUtensorMap make_map(EncodeTiledFn fn, const void* base, int rank, const cuuint64_t* dims, const cuuint64_t* strides, const cuuint32_t* box, CUtensorMapSwizzle sw) {
  CUtensorMap m;
  const cuuint32_t es[3] = {1, 1, 1};
  CUresult rc = fn(&m, CU_TENSOR_MAP_DATA_TYPE_BFLOAT16, rank, const_cast<void*>(base), dims, strides, box, es, CU_TENSOR_MAP_INTERLEAVE_NONE, sw,
     CU_TENSOR_MAP_L2_PROMOTION_L2_128B, CU_TENSOR_MAP_FLOAT_OOB_FILL_NONE);
  (void)rc;
  return m;
}

}

extern "C" void kernel_launch(void* const* d_in, const int* in_sizes, int n_in, void* d_out, int out_size) {
  const __nv_bfloat16* x = static_cast<const __nv_bfloat16*>(d_in[0]);
  const __nv_bfloat16* wqkv = static_cast<const __nv_bfloat16*>(d_in[1]);
  const __nv_bfloat16* wo = static_cast<const __nv_bfloat16*>(d_in[2]);
  const __nv_bfloat16* w1 = static_cast<const __nv_bfloat16*>(d_in[4]);
  const __nv_bfloat16* b1 = static_cast<const __nv_bfloat16*>(d_in[5]);
  const __nv_bfloat16* w2 = static_cast<const __nv_bfloat16*>(d_in[6]);
  const __nv_bfloat16* b2 = static_cast<const __nv_bfloat16*>(d_in[7]);
  __nv_bfloat16* out = static_cast<__nv_bfloat16*>(d_out);

  static EncodeTiledFn encode = nullptr;
  if (!encode) {
    void* fn = nullptr;
    cudaDriverEntryPointQueryResult qr;
    cudaGetDriverEntryPoint("cuTensorMapEncodeTiled", &fn, cudaEnableDefault, &qr);
    encode = reinterpret_cast<EncodeTiledFn>(fn);
    cudaFuncSetAttribute(k1_proj, cudaFuncAttributeMaxDynamicSharedMemorySize, K1_SMEM);
    cudaFuncSetAttribute(k2_attn, cudaFuncAttributeMaxDynamicSharedMemorySize, K2_SMEM);
    cudaFuncSetAttribute(k3_out, cudaFuncAttributeMaxDynamicSharedMemorySize, K3_SMEM);
  }
  CUtensorMap tmX, tmWqkv, tmW1, tmW2, tmWo;
  { const cuuint64_t d[2] = {DM, S_LEN}, st[1] = {DM * 2}; const cuuint32_t b[2] = {64, 128}; tmX = make_map(encode, x, 2, d, st, b, CU_TENSOR_MAP_SWIZZLE_128B); }
  { const cuuint64_t d[2] = {NQKV, DM}, st[1] = {NQKV * 2}; const cuuint32_t b[2] = {64, 32}; tmWqkv = make_map(encode, wqkv, 2, d, st, b, CU_TENSOR_MAP_SWIZZLE_128B); }
  { const cuuint64_t d[2] = {FF, DM}, st[1] = {FF * 2}; const cuuint32_t b[2] = {64, 32}; tmW1 = make_map(encode, w1, 2, d, st, b, CU_TENSOR_MAP_SWIZZLE_128B); }
  { const cuuint64_t d[3] = {16, FF, DM / 16}, st[2] = {DM * 2, 32}; const cuuint32_t b[3] = {16, 64, 5}; tmW2 = make_map(encode, w2, 3, d, st, b, CU_TENSOR_MAP_SWIZZLE_32B); }
  { const cuuint64_t d[3] = {16, DM, DM / 16}, st[2] = {DM * 2, 32}; const cuuint32_t b[3] = {16, 64, 5}; tmWo = make_map(encode, wo, 3, d, st, b, CU_TENSOR_MAP_SWIZZLE_32B); }

  cudaStream_t st = cudaStreamPerThread;
  cudaLaunchAttribute at[2];
  at[0].id = cudaLaunchAttributeClusterDimension; at[0].val.clusterDim.x = 2; at[0].val.clusterDim.y = 1; at[0].val.clusterDim.z = 1;
  at[1].id = cudaLaunchAttributeProgrammaticStreamSerialization; at[1].val.programmaticStreamSerializationAllowed = 1;
  cudaLaunchConfig_t cfg = {};
  cfg.stream = st;
  cfg.gridDim = dim3(128); cfg.blockDim = dim3(384); cfg.dynamicSmemBytes = K1_SMEM; cfg.attrs = at; cfg.numAttrs = 1;
  cudaLaunchKernelEx(&cfg, k1_proj, tmX, tmWqkv, tmW1, x, wqkv, w1, b1);
  cfg.blockDim = dim3(512); cfg.dynamicSmemBytes = K2_SMEM; cfg.attrs = at + 1; cfg.numAttrs = 1;
  cudaLaunchKernelEx(&cfg, k2_attn);
  cfg.blockDim = dim3(288); cfg.dynamicSmemBytes = K3_SMEM; cfg.attrs = at; cfg.numAttrs = 2;
  cudaLaunchKernelEx(&cfg, k3_out, tmW2, tmWo, x, b2, out);
}
```

```cpp
#include <cuda_runtime.h>
#include <cuda_bf16.h>
#include <cuda.h>
#include <stdint.h>

namespace {

constexpr int S_LEN = 2048, DM = 640, NH = 32, FF = 1536, NQKV = 1920;
constexpr float LN_EPS = 1e-5f;

__device__ __align__(1024) __nv_bfloat16 g_qkv[3 * NH * 256 * 192];
__device__ __align__(1024) __nv_bfloat16 g_hid[16 * 24 * 8192];
__device__ __align__(1024) __nv_bfloat16 g_att[16 * 10 * 8192];
__device__ float2 g_rowstat[2 * S_LEN];
__device__ float2 g_colsum[NQKV + FF];
__device__ float g_knorm[NH * 128];
__device__ float g_vmax[NH * 128];
__device__ unsigned g_epoch;
__device__ unsigned g_cnt[6 * 32];

#define TRACE(k, i)

__device__ __forceinline__ uint32_t smem_u32(const void* p) { return (uint32_t)__cvta_generic_to_shared(p); }
__device__ __forceinline__ void wg_fence() { asm volatile("wgmma.fence.sync.aligned;" ::: "memory"); }
__device__ __forceinline__ void wg_commit() { asm volatile("wgmma.commit_group.sync.aligned;" ::: "memory"); }
template <int N> __device__ __forceinline__ void wg_wait() { asm volatile("wgmma.wait_group.sync.aligned %0;" ::"n"(N) : "memory"); }
__device__ __forceinline__ void mbar_init(uint32_t bar, int cnt) { asm volatile("mbarrier.init.shared::cta.b64 [%0], %1;" ::"r"(bar), "r"(cnt)); }
__device__ __forceinline__ void mbar_expect(uint32_t bar, uint32_t bytes) {
  asm volatile("mbarrier.arrive.expect_tx.shared::cta.b64 _, [%0], %1;" ::"r"(bar), "r"(bytes) : "memory");
}
__device__ __forceinline__ void mbar_arrive(uint32_t bar) { asm volatile("mbarrier.arrive.shared::cta.b64 _, [%0];" ::"r"(bar) : "memory"); }
__device__ __forceinline__ void mbar_arrive_cta(uint32_t bar, uint32_t cta) {
  asm volatile("{\n.reg .b32 r;\nmapa.shared::cluster.u32 r, %0, %1;\nmbarrier.arrive.shared::cluster.b64 _, [r];\n}" ::"r"(bar), "r"(cta) : "memory");
}
__device__ __forceinline__ void mbar_wait(uint32_t bar, uint32_t parity) {
  asm volatile("{\n.reg .pred p;\nWAIT:\nmbarrier.try_wait.parity.shared::cta.b64 p, [%0], %1;\n@p bra DONE;\nbra WAIT;\nDONE:\n}" ::"r"(bar), "r"(parity) : "memory");
}
__device__ __forceinline__ void bulk_load(uint32_t dst, const void* src, uint32_t bytes, uint32_t bar) {
  asm volatile("cp.async.bulk.shared::cluster.global.mbarrier::complete_tx::bytes [%0], [%1], %2, [%3];" ::"r"(dst), "l"(src), "r"(bytes), "r"(bar) : "memory");
}
__device__ __forceinline__ void bulk_load_mc(uint32_t dst, const void* src, uint32_t bytes, uint32_t bar, uint16_t mask) {
  asm volatile("cp.async.bulk.shared::cluster.global.mbarrier::complete_tx::bytes.multicast::cluster [%0], [%1], %2, [%3], %4;" ::"r"(dst), "l"(src), "r"(bytes), "r"(bar), "h"(mask) : "memory");
}
__device__ __forceinline__ void tma_2d(uint32_t dst, const CUtensorMap* tm, int c0, int c1, uint32_t bar) {
  asm volatile("cp.async.bulk.tensor.2d.shared::cluster.global.mbarrier::complete_tx::bytes [%0], [%1, {%3, %4}], [%2];" ::"r"(dst), "l"(tm), "r"(bar), "r"(c0), "r"(c1) : "memory");
}
__device__ __forceinline__ void tma_2d_mc(uint32_t dst, const CUtensorMap* tm, int c0, int c1, uint32_t bar, uint16_t mask) {
  asm volatile("cp.async.bulk.tensor.2d.shared::cluster.global.mbarrier::complete_tx::bytes.multicast::cluster [%0], [%1, {%3, %4}], [%2], %5;" ::"r"(dst), "l"(tm), "r"(bar), "r"(c0), "r"(c1), "h"(mask) : "memory");
}
__device__ __forceinline__ void tma_3d_mc(uint32_t dst, const CUtensorMap* tm, int c0, int c1, int c2, uint32_t bar, uint16_t mask) {
  asm volatile("cp.async.bulk.tensor.3d.shared::cluster.global.mbarrier::complete_tx::bytes.multicast::cluster [%0], [%1, {%3, %4, %5}], [%2], %6;" ::"r"(dst), "l"(tm), "r"(bar), "r"(c0), "r"(c1), "r"(c2), "h"(mask) : "memory");
}
__device__ __forceinline__ void cluster_sync() { asm volatile("barrier.cluster.arrive.release.aligned;\nbarrier.cluster.wait.acquire.aligned;" ::: "memory"); }
__device__ __forceinline__ void bar_sync(int id, int n) { asm volatile("bar.sync %0, %1;" ::"r"(id), "r"(n) : "memory"); }
__device__ __forceinline__ float ex2(float x) { float y; asm("ex2.approx.ftz.f32 %0, %1;" : "=f"(y) : "f"(x)); return y; }
__device__ __forceinline__ float tanh_fast(float x) { float y; asm("tanh.approx.f32 %0, %1;" : "=f"(y) : "f"(x)); return y; }
__device__ __forceinline__ uint32_t pack_bf16(float lo, float hi) { uint32_t r; asm("cvt.rn.bf16x2.f32 %0, %1, %2;" : "=r"(r) : "f"(hi), "f"(lo)); return r; }
__device__ __forceinline__ uint32_t hfma2_bf16(uint32_t a, uint32_t b, uint32_t c) { uint32_t r; asm("fma.rn.bf16x2 %0, %1, %2, %3;" : "=r"(r) : "r"(a), "r"(b), "r"(c)); return r; }
__device__ __forceinline__ uint32_t hmul2_bf16(uint32_t a, uint32_t b) { uint32_t r; asm("mul.rn.bf16x2 %0, %1, %2;" : "=r"(r) : "r"(a), "r"(b)); return r; }
template <int LUT> __device__ __forceinline__ uint32_t lop3(uint32_t a, uint32_t b, uint32_t c) {
  uint32_t r; asm("lop3.b32 %0, %1, %2, %3, %4;" : "=r"(r) : "r"(a), "r"(b), "r"(c), "n"(LUT)); return r;
}
__device__ __forceinline__ float bf_lo(uint32_t v) { return __uint_as_float(v << 16); }
__device__ __forceinline__ float bf_hi(uint32_t v) { return __uint_as_float(v & 0xFFFF0000u); }

__device__ __forceinline__ void wgmma_n120_ss(float (&d)[60], uint32_t alo, uint32_t ahi, uint32_t blo, uint32_t bhi, int scaleD) {
  asm volatile("{\n.reg .pred p;\n.reg .b64 da, db;\nsetp.ne.b32 p, %64, 0;\nmov.b64 da, {%60, %61};\nmov.b64 db, {%62, %63};\n"
    "wgmma.mma_async.sync.aligned.m64n120k16.f32.bf16.bf16 "
    "{%0,%1,%2,%3,%4,%5,%6,%7,%8,%9,%10,%11,%12,%13,%14,%15,%16,%17,%18,%19,%20,%21,%22,%23,%24,%25,%26,%27,%28,%29,%30,%31,%32,%33,%34,%35,%36,%37,%38,%39,%40,%41,%42,%43,%44,%45,%46,%47,%48,%49,%50,%51,%52,%53,%54,%55,%56,%57,%58,%59}, "
    "da, db, p, 1, 1, 0, 1;\n}\n"
    :
      "+f"(d[0]), "+f"(d[1]), "+f"(d[2]), "+f"(d[3]), "+f"(d[4]), "+f"(d[5]), "+f"(d[6]), "+f"(d[7]),
      "+f"(d[8]), "+f"(d[9]), "+f"(d[10]), "+f"(d[11]), "+f"(d[12]), "+f"(d[13]), "+f"(d[14]), "+f"(d[15]),
      "+f"(d[16]), "+f"(d[17]), "+f"(d[18]), "+f"(d[19]), "+f"(d[20]), "+f"(d[21]), "+f"(d[22]), "+f"(d[23]),
      "+f"(d[24]), "+f"(d[25]), "+f"(d[26]), "+f"(d[27]), "+f"(d[28]), "+f"(d[29]), "+f"(d[30]), "+f"(d[31]),
      "+f"(d[32]), "+f"(d[33]), "+f"(d[34]), "+f"(d[35]), "+f"(d[36]), "+f"(d[37]), "+f"(d[38]), "+f"(d[39]),
      "+f"(d[40]), "+f"(d[41]), "+f"(d[42]), "+f"(d[43]), "+f"(d[44]), "+f"(d[45]), "+f"(d[46]), "+f"(d[47]),
      "+f"(d[48]), "+f"(d[49]), "+f"(d[50]), "+f"(d[51]), "+f"(d[52]), "+f"(d[53]), "+f"(d[54]), "+f"(d[55]),
      "+f"(d[56]), "+f"(d[57]), "+f"(d[58]), "+f"(d[59])
    : "r"(alo), "r"(ahi), "r"(blo), "r"(bhi), "r"(scaleD));
}
__device__ __forceinline__ void wgmma_n96_ss(float (&d)[48], uint32_t alo, uint32_t ahi, uint32_t blo, uint32_t bhi, int scaleD) {
  asm volatile("{\n.reg .pred p;\n.reg .b64 da, db;\nsetp.ne.b32 p, %52, 0;\nmov.b64 da, {%48, %49};\nmov.b64 db, {%50, %51};\n"
    "wgmma.mma_async.sync.aligned.m64n96k16.f32.bf16.bf16 "
    "{%0,%1,%2,%3,%4,%5,%6,%7,%8,%9,%10,%11,%12,%13,%14,%15,%16,%17,%18,%19,%20,%21,%22,%23,%24,%25,%26,%27,%28,%29,%30,%31,%32,%33,%34,%35,%36,%37,%38,%39,%40,%41,%42,%43,%44,%45,%46,%47}, "
    "da, db, p, 1, 1, 0, 1;\n}\n"
    :
      "+f"(d[0]), "+f"(d[1]), "+f"(d[2]), "+f"(d[3]), "+f"(d[4]), "+f"(d[5]), "+f"(d[6]), "+f"(d[7]),
      "+f"(d[8]), "+f"(d[9]), "+f"(d[10]), "+f"(d[11]), "+f"(d[12]), "+f"(d[13]), "+f"(d[14]), "+f"(d[15]),
      "+f"(d[16]), "+f"(d[17]), "+f"(d[18]), "+f"(d[19]), "+f"(d[20]), "+f"(d[21]), "+f"(d[22]), "+f"(d[23]),
      "+f"(d[24]), "+f"(d[25]), "+f"(d[26]), "+f"(d[27]), "+f"(d[28]), "+f"(d[29]), "+f"(d[30]), "+f"(d[31]),
      "+f"(d[32]), "+f"(d[33]), "+f"(d[34]), "+f"(d[35]), "+f"(d[36]), "+f"(d[37]), "+f"(d[38]), "+f"(d[39]),
      "+f"(d[40]), "+f"(d[41]), "+f"(d[42]), "+f"(d[43]), "+f"(d[44]), "+f"(d[45]), "+f"(d[46]), "+f"(d[47])
    : "r"(alo), "r"(ahi), "r"(blo), "r"(bhi), "r"(scaleD));
}
__device__ __forceinline__ void wgmma_n80_ss(float (&d)[40], uint32_t alo, uint32_t ahi, uint32_t blo, uint32_t bhi, int scaleD) {
  asm volatile("{\n.reg .pred p;\n.reg .b64 da, db;\nsetp.ne.b32 p, %44, 0;\nmov.b64 da, {%40, %41};\nmov.b64 db, {%42, %43};\n"
    "wgmma.mma_async.sync.aligned.m64n80k16.f32.bf16.bf16 "
    "{%0,%1,%2,%3,%4,%5,%6,%7,%8,%9,%10,%11,%12,%13,%14,%15,%16,%17,%18,%19,%20,%21,%22,%23,%24,%25,%26,%27,%28,%29,%30,%31,%32,%33,%34,%35,%36,%37,%38,%39}, "
    "da, db, p, 1, 1, 0, 1;\n}\n"
    :
      "+f"(d[0]), "+f"(d[1]), "+f"(d[2]), "+f"(d[3]), "+f"(d[4]), "+f"(d[5]), "+f"(d[6]), "+f"(d[7]),
      "+f"(d[8]), "+f"(d[9]), "+f"(d[10]), "+f"(d[11]), "+f"(d[12]), "+f"(d[13]), "+f"(d[14]), "+f"(d[15]),
      "+f"(d[16]), "+f"(d[17]), "+f"(d[18]), "+f"(d[19]), "+f"(d[20]), "+f"(d[21]), "+f"(d[22]), "+f"(d[23]),
      "+f"(d[24]), "+f"(d[25]), "+f"(d[26]), "+f"(d[27]), "+f"(d[28]), "+f"(d[29]), "+f"(d[30]), "+f"(d[31]),
      "+f"(d[32]), "+f"(d[33]), "+f"(d[34]), "+f"(d[35]), "+f"(d[36]), "+f"(d[37]), "+f"(d[38]), "+f"(d[39])
    : "r"(alo), "r"(ahi), "r"(blo), "r"(bhi), "r"(scaleD));
}
__device__ __forceinline__ void wgmma_n64_rs(float (&d)[32], uint32_t a0, uint32_t a1, uint32_t a2, uint32_t a3, uint32_t blo, uint32_t bhi, int scaleD) {
  asm volatile("{\n.reg .pred p;\n.reg .b64 db;\nsetp.ne.b32 p, %38, 0;\nmov.b64 db, {%36, %37};\n"
    "wgmma.mma_async.sync.aligned.m64n64k16.f32.bf16.bf16 "
    "{%0,%1,%2,%3,%4,%5,%6,%7,%8,%9,%10,%11,%12,%13,%14,%15,%16,%17,%18,%19,%20,%21,%22,%23,%24,%25,%26,%27,%28,%29,%30,%31}, "
    "{%32, %33, %34, %35}, db, p, 1, 1, 0;\n}\n"
    :
      "+f"(d[0]), "+f"(d[1]), "+f"(d[2]), "+f"(d[3]), "+f"(d[4]), "+f"(d[5]), "+f"(d[6]), "+f"(d[7]),
      "+f"(d[8]), "+f"(d[9]), "+f"(d[10]), "+f"(d[11]), "+f"(d[12]), "+f"(d[13]), "+f"(d[14]), "+f"(d[15]),
      "+f"(d[16]), "+f"(d[17]), "+f"(d[18]), "+f"(d[19]), "+f"(d[20]), "+f"(d[21]), "+f"(d[22]), "+f"(d[23]),
      "+f"(d[24]), "+f"(d[25]), "+f"(d[26]), "+f"(d[27]), "+f"(d[28]), "+f"(d[29]), "+f"(d[30]), "+f"(d[31])
    : "r"(a0), "r"(a1), "r"(a2), "r"(a3), "r"(blo), "r"(bhi), "r"(scaleD));
}
__device__ __forceinline__ void wgmma_n24_rs(float (&d)[12], uint32_t a0, uint32_t a1, uint32_t a2, uint32_t a3, uint32_t blo, uint32_t bhi, int scaleD) {
  asm volatile("{\n.reg .pred p;\n.reg .b64 db;\nsetp.ne.b32 p, %18, 0;\nmov.b64 db, {%16, %17};\n"
    "wgmma.mma_async.sync.aligned.m64n24k16.f32.bf16.bf16 "
    "{%0,%1,%2,%3,%4,%5,%6,%7,%8,%9,%10,%11}, "
    "{%12, %13, %14, %15}, db, p, 1, 1, 1;\n}\n"
    :
      "+f"(d[0]), "+f"(d[1]), "+f"(d[2]), "+f"(d[3]), "+f"(d[4]), "+f"(d[5]), "+f"(d[6]), "+f"(d[7]),
      "+f"(d[8]), "+f"(d[9]), "+f"(d[10]), "+f"(d[11])
    : "r"(a0), "r"(a1), "r"(a2), "r"(a3), "r"(blo), "r"(bhi), "r"(scaleD));
}

constexpr uint32_t MUFU_MASK = 0x4949;
constexpr float QSCALE = 0.22360679774997896f * 1.4426950408889634f;
constexpr float FAST_BOUND2 = 3600.f;
constexpr float FAST_VMAX = 1.0e15f;

#define SLAB_A_AT 1
#define SLAB_B_AT 8
constexpr int AB_STAGE = 49152;
constexpr int KV_TILE = 12288;
constexpr int D_STAGE = 28672;
constexpr int SM_SLAB = 196608;
constexpr int SM_PARAM = SM_SLAB + 20480;
constexpr int SM_RED = SM_PARAM + 4608;
constexpr int SM_BARS = SM_RED + 512;
constexpr int SMEM_BYTES = SM_BARS + 512;
constexpr int B_FULL = 0, B_EMPTY = 32, B_PREADY = 64, B_SLAB = 80, B_SLABFREE = 96, B_QKV = 104, B_KV = 112, B_KVFREE = 240, B_DFULL = 288, B_DEMPTY = 336;
constexpr int NB_WG = 1, NB_QKV = 6, NB_HID = 7, NB_ATT = 8, NB_HELP = 9, NB_FIN = 10;

__device__ __forceinline__ void st_tagged(float2* p, float v, float tag) {
  asm volatile("{\n.reg .b64 v;\nmov.b64 v, {%1, %2};\nst.relaxed.gpu.global.b64 [%0], v;\n}" ::"l"(p), "f"(v), "f"(tag) : "memory");
}
__device__ __forceinline__ bool ld_tagged(const float2* p, float& v, float tag) {
  float tg;
  asm volatile("{\n.reg .b64 v;\nld.relaxed.gpu.global.b64 v, [%2];\nmov.b64 {%0, %1}, v;\n}" : "=f"(v), "=f"(tg) : "l"(p) : "memory");
  return __float_as_uint(tg) == __float_as_uint(tag);
}
__device__ __forceinline__ void wait_counter(const unsigned* cnt, unsigned target) {
  unsigned cur; int spins = 0;
  do { asm volatile("ld.acquire.gpu.global.u32 %0, [%1];" : "=r"(cur) : "l"(cnt) : "memory"); } while ((int)(cur - target) < 0 && ++spins < (1 << 22));
  asm volatile("fence.proxy.async.global;" ::: "memory");
}

__device__ __forceinline__ uint32_t exp2_pair(float ta, float tb, uint32_t one2) {
  const uint32_t v = __byte_perm(__float_as_uint(ta), __float_as_uint(tb), 0x6521);
  const uint32_t m = lop3<0xEA>(v, 0x007F007Fu, one2);
  const uint32_t q = hfma2_bf16(m, 0xBDF4BDF4u, 0x3EB43EB4u);
  const uint32_t p = hfma2_bf16(q, m, 0xBF3BBF3Bu);
  return hmul2_bf16(v, p);
}
__device__ __forceinline__ void exp_tile(const float (&s)[32], uint32_t (&p)[16], const uint32_t mask, uint32_t one2) {
  #pragma unroll
  for (int i = 0; i < 8; i++) {
    if ((mask >> i) & 1) {
      p[2 * i] = pack_bf16(ex2(s[4 * i]), ex2(s[4 * i + 1]));
      p[2 * i + 1] = pack_bf16(ex2(s[4 * i + 2]), ex2(s[4 * i + 3]));
    } else {
      p[2 * i] = exp2_pair(s[4 * i], s[4 * i + 1], one2);
      p[2 * i + 1] = exp2_pair(s[4 * i + 2], s[4 * i + 3], one2);
    }
  }
}
__device__ __forceinline__ void issue_qk(float (&s)[32], const uint32_t (&qa)[8], uint32_t klo) {
  wgmma_n64_rs(s, qa[0], qa[1], qa[2], qa[3], klo | (8u << 16), 24u, 0);
  wgmma_n64_rs(s, qa[4], qa[5], qa[6], qa[7], klo + 16u, 24u, 1);
}
__device__ __forceinline__ void issue_pv(float (&o)[12], const uint32_t (&p)[16], uint32_t vlo) {
  #pragma unroll
  for (int kk = 0; kk < 4; kk++) wgmma_n24_rs(o, p[4 * kk], p[4 * kk + 1], p[4 * kk + 2], p[4 * kk + 3], vlo + kk * 48u, 8u, 1);
}

struct Maps { CUtensorMap x, wqkv, w1, sq, s1, w2, wo; };

__global__ void __launch_bounds__(640, 1)
fused_block(const __grid_constant__ Maps tm, const __nv_bfloat16* __restrict__ x, const __nv_bfloat16* __restrict__ b1,
            const __nv_bfloat16* __restrict__ w2, const __nv_bfloat16* __restrict__ wo, const __nv_bfloat16* __restrict__ b2,
            __nv_bfloat16* __restrict__ out) {
  extern __shared__ __align__(1024) uint8_t smem[];
  const uint32_t sb = smem_u32(smem);
  const uint32_t sd = sb & 0x3FFFF;
  const uint32_t bar = sb + SM_BARS;
  float* s_cs = reinterpret_cast<float*>(smem + SM_PARAM);
  float* s_cs1 = s_cs + 240;
  float* s_b1h = s_cs1 + 192;
  float4* s_row = reinterpret_cast<float4*>(smem + SM_PARAM + 2560);
  const int tid = threadIdx.x, lane = tid & 31;
  const int warp = __shfl_sync(~0u, tid >> 5, 0), wg = warp >> 2;
  const int bid = blockIdx.x, rank = bid & 1;
  const int cbA = (bid >> 1) & 7, rbA = ((bid >> 4) << 1) | rank;
  const int hd = bid >> 2, qq = bid & 3;
  const int rbD = bid >> 3, cbD = bid & 7;

  if (tid == 0) TRACE(0, 0);
  if (tid == 0) {
    for (int s = 0; s < 4; s++) { mbar_init(bar + B_FULL + 8 * s, 1); mbar_init(bar + B_EMPTY + 8 * s, 32); }
    mbar_init(bar + B_PREADY, 64); mbar_init(bar + B_PREADY + 8, 64); mbar_init(bar + B_SLAB, 1); mbar_init(bar + B_SLAB + 8, 1);
    mbar_init(bar + B_SLABFREE, 64); mbar_init(bar + B_QKV, 1);
    for (int j = 0; j < 16; j++) mbar_init(bar + B_KV + 8 * j, 1);
    for (int s = 0; s < 6; s++) { mbar_init(bar + B_KVFREE + 8 * s, 32); mbar_init(bar + B_DFULL + 8 * s, 1); mbar_init(bar + B_DEMPTY + 8 * s, 16); }
    asm volatile("fence.mbarrier_init.release.cluster;" ::: "memory");
  }
  if (tid == 512) {
    asm volatile("prefetch.tensormap [%0];" ::"l"(&tm.x) : "memory");
    asm volatile("prefetch.tensormap [%0];" ::"l"(&tm.wqkv) : "memory");
    asm volatile("prefetch.tensormap [%0];" ::"l"(&tm.sq) : "memory");
  }
  const unsigned epoch = __ldcg(&g_epoch) + 1u;
  const float tag = __uint_as_float(epoch);
  __syncthreads();
  cluster_sync();

  if (wg == 4) {
    asm volatile("setmaxnreg.dec.sync.aligned.u32 32;");
    if (warp == 16) {
      if (lane == 0) {
        int s = 0; uint32_t ph = 1;
        #pragma unroll 1
        for (int it = 0; it < 20; it++) {
          const int kb = it < 10 ? it : it - 10;
          mbar_wait(bar + B_EMPTY + 8 * s, ph);
          const uint32_t sa = sb + s * AB_STAGE, sw = sa + 16384, fb = bar + B_FULL + 8 * s;
          if (it < 10) {
            mbar_expect(fb, 16384 + 32768);
            tma_2d(sa, &tm.x, kb * 64, rbA * 128, fb);
            for (int b = 0; b < 4; b++) tma_2d_mc(sw + b * 8192 + rank * 4096, &tm.wqkv, cbA * 240 + b * 64 - (b >> 1) * 8, kb * 64 + rank * 32, fb, 3);
          } else {
            mbar_expect(fb, 16384 + 24576);
            tma_2d(sa, &tm.x, kb * 64, rbA * 128, fb);
            tma_3d_mc(sw + rank * 12288, &tm.w1, 0, kb * 64 + rank * 32, cbA * 6, fb, 3);
          }
          if (it == SLAB_A_AT && bid < 120) {
            mbar_expect(bar + B_SLAB, 20480);
            for (int i = 0; i < 4; i++) tma_2d(sb + SM_SLAB + i * 5120, &tm.sq, bid * 16, i * 160, bar + B_SLAB);
          }
          if (it == SLAB_B_AT && bid < 96) {
            mbar_wait(bar + B_SLABFREE, 0);
            mbar_expect(bar + B_SLAB + 8, 20480);
            for (int i = 0; i < 4; i++) tma_2d(sb + SM_SLAB + i * 5120, &tm.s1, bid * 16, i * 160, bar + B_SLAB + 8);
          }
          if (++s == 4) { s = 0; ph ^= 1; }
        }
        wait_counter(&g_cnt[0], epoch * 128u);
        mbar_arrive(bar + B_QKV);
        const uint8_t* ksrc = reinterpret_cast<const uint8_t*>(g_qkv + (size_t)(NH + hd) * 256 * 192);
        const uint8_t* vsrc = reinterpret_cast<const uint8_t*>(g_qkv + (size_t)(2 * NH + hd) * 256 * 192);
        #pragma unroll 1
        for (int j = 0; j < 16; j++) {
          if ((j & 3) == 0) mbar_wait(bar + B_EMPTY + 8 * (j >> 2), ph);
          mbar_expect(bar + B_KV + 8 * j, KV_TILE);
          bulk_load(sb + j * KV_TILE, ksrc + j * 6144, 6144, bar + B_KV + 8 * j);
          bulk_load(sb + j * KV_TILE + 6144, vsrc + j * 6144, 6144, bar + B_KV + 8 * j);
        }
        if (tid == 512) TRACE(0, 9);
        asm volatile("cp.async.bulk.prefetch.L2.global [%0], %1;" ::"l"((const uint8_t*)w2 + (size_t)bid * (FF * DM * 2 / 128)), "r"(FF * DM * 2 / 128) : "memory");
        asm volatile("cp.async.bulk.prefetch.L2.global [%0], %1;" ::"l"((const uint8_t*)wo + (size_t)bid * (DM * DM * 2 / 128)), "r"(DM * DM * 2 / 128) : "memory");
        wait_counter(&g_cnt[32], epoch * 128u);
        s = 0; ph = 1;
        #pragma unroll 1
        for (int kb = 0; kb < 34; kb++) {
          if (kb == 24) {
            wait_counter(&g_cnt[64 + 32 * (rbD >> 2)], epoch * 32u);
            if (bid == 0) g_epoch = epoch;
          }
          if (kb < 6) mbar_wait(bar + B_KVFREE + 8 * s, 0); else mbar_wait(bar + B_DEMPTY + 8 * s, ph);
          const uint32_t sa = sb + s * D_STAGE, fb = bar + B_DFULL + 8 * s;
          mbar_expect(fb, D_STAGE);
          const __nv_bfloat16* asrc = kb < 24 ? g_hid + (size_t)(rbD * 24 + kb) * 8192 : g_att + (size_t)(rbD * 10 + kb - 24) * 8192;
          bulk_load_mc(sa + rank * 8192, asrc + rank * 4096, 8192, fb, 3);
          const CUtensorMap* tw = kb < 24 ? &tm.w2 : &tm.wo;
          const int k0 = (kb < 24 ? kb : kb - 24) * 64;
          for (int b = 0; b < 3; b++) tma_2d(sa + 16384 + b * 4096, tw, cbD * 80 + b * 32, k0, fb);
          if (++s == 6) { s = 0; ph ^= 1; }
        }
      }
    } else {
      if (warp == 19) {
        bar_sync(NB_QKV, 544);
        if (lane == 0) { __threadfence(); atomicAdd(&g_cnt[0], 1u); }
        __syncwarp();
        bar_sync(NB_HID, 544);
        if (lane == 0) { __threadfence(); atomicAdd(&g_cnt[32], 1u); }
        __syncwarp();
        bar_sync(NB_ATT, 544);
        if (lane == 0) { __threadfence(); atomicAdd(&g_cnt[64 + 32 * qq], 1u); }
        __syncwarp();
      } else {
        const int w = warp - 17, t64 = tid - 544;
        float* s_red = reinterpret_cast<float*>(smem + SM_RED);
        auto slab_sum = [&](uint32_t fullbar, float2* dst) {
          mbar_wait(fullbar, 0);
          float a[8];
          #pragma unroll
          for (int i = 0; i < 8; i++) a[i] = 0.f;
          #pragma unroll 2
          for (int i = w; i < 40; i += 2) {
            const uint4 u = *reinterpret_cast<const uint4*>(smem + SM_SLAB + i * 512 + lane * 16);
            a[0] += bf_lo(u.x); a[1] += bf_hi(u.x); a[2] += bf_lo(u.y); a[3] += bf_hi(u.y);
            a[4] += bf_lo(u.z); a[5] += bf_hi(u.z); a[6] += bf_lo(u.w); a[7] += bf_hi(u.w);
          }
          #pragma unroll
          for (int i = 0; i < 4; i++) { const bool up = lane & 2; const float snd = up ? a[i] : a[i + 4]; a[i] = (up ? a[i + 4] : a[i]) + __shfl_xor_sync(~0u, snd, 2); }
          #pragma unroll
          for (int i = 0; i < 2; i++) { const bool up = lane & 4; const float snd = up ? a[i] : a[i + 2]; a[i] = (up ? a[i + 2] : a[i]) + __shfl_xor_sync(~0u, snd, 4); }
          { const bool up = lane & 8; const float snd = up ? a[0] : a[1]; a[0] = (up ? a[1] : a[0]) + __shfl_xor_sync(~0u, snd, 8); }
          a[0] += __shfl_xor_sync(~0u, a[0], 16);
          if (lane < 16) s_red[w * 16 + (lane & 1) * 8 + ((lane >> 1) & 1) * 4 + ((lane >> 2) & 1) * 2 + (lane >> 3)] = a[0];
          bar_sync(NB_HELP, 64);
          if (t64 < 16) st_tagged(dst + t64, s_red[t64] + s_red[16 + t64], tag);
          bar_sync(NB_HELP, 64);
        };
        if (bid < 120) slab_sum(bar + B_SLAB, g_colsum + bid * 16);
        mbar_arrive(bar + B_SLABFREE);
        {
          const float2* pc = g_colsum + cbA * 240 + t64;
          const int i3 = t64 < 48 ? 192 : 0;
          float c0, c1, c2, c3; bool ok; int spins = 0;
          do { ok = ld_tagged(pc, c0, tag); ok &= ld_tagged(pc + 64, c1, tag); ok &= ld_tagged(pc + 128, c2, tag); ok &= ld_tagged(pc + i3, c3, tag); } while (!ok && ++spins < (1 << 20));
          s_cs[t64] = c0; s_cs[64 + t64] = c1; s_cs[128 + t64] = c2; if (t64 < 48) s_cs[192 + t64] = c3;
        }
        {
          const float2* pr = g_rowstat + 2 * (rbA * 128 + t64);
          float m0, v0, m1, v1; bool ok; int spins = 0;
          do { ok = ld_tagged(pr, m0, tag); ok &= ld_tagged(pr + 1, v0, tag); ok &= ld_tagged(pr + 128, m1, tag); ok &= ld_tagged(pr + 129, v1, tag); } while (!ok && ++spins < (1 << 20));
          const float ra = 1.f / sqrtf(v0 + LN_EPS), rc = 1.f / sqrtf(v1 + LN_EPS);
          s_row[t64] = make_float4(m0, ra, ra / sqrtf(v0 * ra * ra + LN_EPS), 0.f);
          s_row[64 + t64] = make_float4(m1, rc, rc / sqrtf(v1 * rc * rc + LN_EPS), 0.f);
        }
        mbar_arrive(bar + B_PREADY);
        if (t64 == 0) TRACE(0, 8);
        if (bid < 96) slab_sum(bar + B_SLAB + 8, g_colsum + NQKV + bid * 16);
        {
          const float e0 = __bfloat162float(b1[cbA * 192 + t64]), e1 = __bfloat162float(b1[cbA * 192 + 64 + t64]), e2 = __bfloat162float(b1[cbA * 192 + 128 + t64]);
          const float2* pc = g_colsum + NQKV + cbA * 192 + t64;
          float c0, c1, c2; bool ok; int spins = 0;
          do { ok = ld_tagged(pc, c0, tag); ok &= ld_tagged(pc + 64, c1, tag); ok &= ld_tagged(pc + 128, c2, tag); } while (!ok && ++spins < (1 << 20));
          s_cs1[t64] = c0; s_cs1[64 + t64] = c1; s_cs1[128 + t64] = c2;
          s_b1h[t64] = 0.5f * e0; s_b1h[64 + t64] = 0.5f * e1; s_b1h[128 + t64] = 0.5f * e2;
        }
        mbar_arrive(bar + B_PREADY + 8);
        if (t64 == 0) TRACE(0, 10);
      }
    }
    cluster_sync();
    return;
  }

  asm volatile("setmaxnreg.inc.sync.aligned.u32 112;");
  const int w4 = warp & 3, g = lane >> 2, t = lane & 3;
  const int mi = wg & 1, ni = wg >> 1;
  {
    const int row = bid * 16 + warp;
    const uint2* px = reinterpret_cast<const uint2*>(x + (size_t)row * DM);
    float v[20], sum = 0.f, sq = 0.f;
    #pragma unroll
    for (int i = 0; i < 5; i++) {
      const uint2 u = __ldg(px + i * 32 + lane);
      v[4 * i] = bf_lo(u.x); v[4 * i + 1] = bf_hi(u.x); v[4 * i + 2] = bf_lo(u.y); v[4 * i + 3] = bf_hi(u.y);
      sum += (v[4 * i] + v[4 * i + 1]) + (v[4 * i + 2] + v[4 * i + 3]);
    }
    #pragma unroll
    for (int o = 16; o; o >>= 1) sum += __shfl_xor_sync(~0u, sum, o);
    const float mean = sum * (1.f / DM);
    #pragma unroll
    for (int i = 0; i < 20; i++) { const float d = v[i] - mean; sq = fmaf(d, d, sq); }
    #pragma unroll
    for (int o = 16; o; o >>= 1) sq += __shfl_xor_sync(~0u, sq, o);
    if (lane < 2) st_tagged(g_rowstat + 2 * row + lane, lane ? sq * (1.f / DM) : mean, tag);
  }
  int s = 0; uint32_t ph = 0;
  const int tg0 = rbA * 16 + mi * 8 + w4 * 2;
  {
    float acc[60];
    #pragma unroll 1
    for (int kb = 0; kb < 10; kb++) {
      mbar_wait(bar + B_FULL + 8 * s, ph);
      if (tid == 0 && kb == 0) TRACE(0, 1);
      const uint32_t alo = ((sd + s * AB_STAGE + mi * 8192) >> 4) | (1u << 16);
      const uint32_t blo = ((sd + s * AB_STAGE + 16384 + ni * 16384) >> 4) | (512u << 16);
      wg_fence();
      #pragma unroll
      for (int k = 0; k < 4; k++) wgmma_n120_ss(acc, alo + k * 2, 64u | (1u << 30), blo + k * 128, 64u | (1u << 30), (kb | k) != 0);
      wg_commit();
      if (kb > 0) { wg_wait<1>(); if (lane < 2) mbar_arrive_cta(bar + B_EMPTY + 8 * ((s + 3) & 3), lane); }
      if (++s == 4) { s = 0; ph ^= 1; }
    }
    wg_wait<0>();
    if (lane < 2) mbar_arrive_cta(bar + B_EMPTY + 8 * ((s + 3) & 3), lane);
    if (tid == 0) TRACE(0, 2);
    mbar_wait(bar + B_PREADY, 0);
    const float4 st0 = s_row[mi * 64 + w4 * 16 + g], st1 = s_row[mi * 64 + w4 * 16 + g + 8];
    const float nm0 = -st0.x, nm1 = -st1.x;
    uint32_t* dbase = reinterpret_cast<uint32_t*>(g_qkv + ((size_t)(cbA * 12 + ni * 6) * 256 + tg0) * 192) + lane;
    const uint32_t kaug0 = ((MUFU_MASK >> (tg0 & 15)) & 1) ? 0u : 0x3B8043C0u;
    const uint32_t kaug1 = ((MUFU_MASK >> ((tg0 + 1) & 15)) & 1) ? 0u : 0x3B8043C0u;
    #pragma unroll
    for (int pi = 0; pi < 3; pi++) {
      const int P = cbA * 6 + ni * 3 + pi, sec = P >> 4;
      const float sc = sec == 0 ? QSCALE : 1.f;
      const float r0 = st0.y * sc, r1 = st1.y * sc;
      uint32_t* de = dbase + pi * 2 * 256 * 96;
      uint32_t* dod = de + 256 * 96;
      uint32_t w[5][2];
      #pragma unroll
      for (int gi = 0; gi < 5; gi++) {
        const int i = pi * 5 + gi;
        const float2 cs = *reinterpret_cast<const float2*>(s_cs + ni * 120 + 8 * i + 2 * t);
        w[gi][0] = pack_bf16(fmaf(nm0, cs.x, acc[4 * i]) * r0, fmaf(nm0, cs.y, acc[4 * i + 1]) * r0);
        w[gi][1] = pack_bf16(fmaf(nm1, cs.x, acc[4 * i + 2]) * r1, fmaf(nm1, cs.y, acc[4 * i + 3]) * r1);
      }
      const uint32_t aug0 = sec == 1 ? kaug0 : (sec == 0 ? 0x3F803F80u : 0x00003F80u);
      const uint32_t aug1 = sec == 1 ? kaug1 : (sec == 0 ? 0x3F803F80u : 0x00003F80u);
      const uint32_t ae0 = t == 2 ? aug0 : 0u, ae1 = t == 2 ? aug1 : 0u, ao0 = t == 0 ? aug0 : 0u, ao1 = t == 0 ? aug1 : 0u;
      de[0] = w[0][0];  de[96] = w[0][1];  de[32] = w[1][0];  de[96 + 32] = w[1][1];
      de[64] = t < 2 ? w[2][0] : ae0;   de[96 + 64] = t < 2 ? w[2][1] : ae1;
      dod[0] = w[3][0]; dod[96] = w[3][1]; dod[32] = w[4][0]; dod[96 + 32] = w[4][1];
      dod[64] = t >= 2 ? w[2][0] : ao0; dod[96 + 64] = t >= 2 ? w[2][1] : ao1;
      if (sec == 1) {
        uint32_t e0 = hfma2_bf16(w[1][0], w[1][0], hmul2_bf16(w[0][0], w[0][0])), e1 = hfma2_bf16(w[1][1], w[1][1], hmul2_bf16(w[0][1], w[0][1]));
        uint32_t o0 = hfma2_bf16(w[4][0], w[4][0], hmul2_bf16(w[3][0], w[3][0])), o1 = hfma2_bf16(w[4][1], w[4][1], hmul2_bf16(w[3][1], w[3][1]));
        if (t < 2) { e0 = hfma2_bf16(w[2][0], w[2][0], e0); e1 = hfma2_bf16(w[2][1], w[2][1], e1); }
        else       { o0 = hfma2_bf16(w[2][0], w[2][0], o0); o1 = hfma2_bf16(w[2][1], w[2][1], o1); }
        float fe0 = bf_lo(e0) + bf_hi(e0), fe1 = bf_lo(e1) + bf_hi(e1), fo0 = bf_lo(o0) + bf_hi(o0), fo1 = bf_lo(o1) + bf_hi(o1);
        #pragma unroll
        for (int o = 1; o < 4; o <<= 1) {
          fe0 += __shfl_xor_sync(~0u, fe0, o); fe1 += __shfl_xor_sync(~0u, fe1, o); fo0 += __shfl_xor_sync(~0u, fo0, o); fo1 += __shfl_xor_sync(~0u, fo1, o);
        }
        const unsigned me = __reduce_max_sync(~0u, max(__float_as_uint(fe0) & 0x7FFFFFFFu, __float_as_uint(fe1) & 0x7FFFFFFFu));
        const unsigned mo = __reduce_max_sync(~0u, max(__float_as_uint(fo0) & 0x7FFFFFFFu, __float_as_uint(fo1) & 0x7FFFFFFFu));
        if (lane == 0) { float* kn = g_knorm + (size_t)(2 * P - 32) * 128 + (tg0 >> 1); kn[0] = __uint_as_float(me); kn[128] = __uint_as_float(mo); }
      } else if (sec == 2) {
        unsigned m = 0;
        #pragma unroll
        for (int gi = 0; gi < 5; gi++) m = __vmaxu2(m, __vmaxu2(w[gi][0] & 0x7FFF7FFFu, w[gi][1] & 0x7FFF7FFFu));
        m = __reduce_max_sync(~0u, max(m << 16, m & 0xFFFF0000u));
        if (lane == 0) { float* vm = g_vmax + (size_t)(2 * P - 64) * 128 + (tg0 >> 1); vm[0] = __uint_as_float(m); vm[128] = __uint_as_float(m); }
      }
    }
    asm volatile("bar.arrive %0, 544;" ::"n"(NB_QKV) : "memory");
  }
  if (tid == 0) TRACE(0, 4);
  uint32_t qa[8];
  unsigned kmax_bits, vmax_bits;
  auto load_q = [&](int tg) {
    const uint32_t* qp = reinterpret_cast<const uint32_t*>(g_qkv + ((size_t)hd * 256 + tg) * 192) + lane;
    qa[0] = __ldcg(qp); qa[1] = __ldcg(qp + 96); qa[2] = __ldcg(qp + 32); qa[3] = __ldcg(qp + 96 + 32);
    qa[4] = __ldcg(qp + 64); qa[5] = __ldcg(qp + 96 + 64); qa[6] = 0; qa[7] = 0;
  };
  {
    float acc[48];
    #pragma unroll 1
    for (int kb = 0; kb < 10; kb++) {
      mbar_wait(bar + B_FULL + 8 * s, ph);
      const uint32_t alo = ((sd + s * AB_STAGE + mi * 8192) >> 4) | (1u << 16);
      const uint32_t blo = ((sd + s * AB_STAGE + 16384 + ni * 3 * 2048) >> 4) | (128u << 16);
      wg_fence();
      #pragma unroll
      for (int k = 0; k < 4; k++) wgmma_n96_ss(acc, alo + k * 2, 64u | (1u << 30), blo + (k >> 1) * 768 + (k & 1) * 64, 32u | (2u << 30), (kb | k) != 0);
      wg_commit();
      if (kb > 0) { wg_wait<1>(); if (lane < 2) mbar_arrive_cta(bar + B_EMPTY + 8 * ((s + 3) & 3), lane); }
      if (++s == 4) { s = 0; ph ^= 1; }
    }
    wg_wait<0>();
    if (lane < 2) mbar_arrive_cta(bar + B_EMPTY + 8 * ((s + 3) & 3), lane);
    if (tid == 0) TRACE(0, 5);
    mbar_wait(bar + B_QKV, 0);
    load_q(qq * 64 + wg * 16 + w4 * 2);
    const float4 kn4 = __ldcg(reinterpret_cast<const float4*>(g_knorm + hd * 128) + lane), vm4 = __ldcg(reinterpret_cast<const float4*>(g_vmax + hd * 128) + lane);
    kmax_bits = max(max(__float_as_uint(kn4.x), __float_as_uint(kn4.y)), max(__float_as_uint(kn4.z), __float_as_uint(kn4.w)));
    vmax_bits = max(max(__float_as_uint(vm4.x), __float_as_uint(vm4.y)), max(__float_as_uint(vm4.z), __float_as_uint(vm4.w)));
    mbar_wait(bar + B_PREADY + 8, 0);
    const float4 st0 = s_row[mi * 64 + w4 * 16 + g], st1 = s_row[mi * 64 + w4 * 16 + g + 8];
    const float nm0 = -st0.x, nm1 = -st1.x, a0 = 0.5f * st0.z, a1 = 0.5f * st1.z;
    uint32_t* dst = reinterpret_cast<uint32_t*>(g_hid + ((size_t)(rbA * 24 + cbA * 3) * 16 + mi * 8 + w4 * 2) * 512) + lane;
    constexpr float GA = 1.5957691216057308f, GB = 1.5957691216057308f * 0.044715f * 4.f;
    #pragma unroll
    for (int i = 0; i < 12; i++) {
      const float2 cs = *reinterpret_cast<const float2*>(s_cs1 + ni * 96 + 8 * i + 2 * t);
      const float2 bb = *reinterpret_cast<const float2*>(s_b1h + ni * 96 + 8 * i + 2 * t);
      float h[4];
      h[0] = fmaf(fmaf(nm0, cs.x, acc[4 * i]), a0, bb.x);     h[1] = fmaf(fmaf(nm0, cs.y, acc[4 * i + 1]), a0, bb.y);
      h[2] = fmaf(fmaf(nm1, cs.x, acc[4 * i + 2]), a1, bb.x); h[3] = fmaf(fmaf(nm1, cs.y, acc[4 * i + 3]), a1, bb.y);
      #pragma unroll
      for (int e = 0; e < 4; e++) {
        const float u = h[e] * fmaf(h[e] * h[e], GB, GA);
        h[e] = fmaf(h[e], tanh_fast(u), h[e]);
      }
      const int kgl = ni * 12 + i;
      uint32_t* d = dst + (kgl >> 3) * 4096 + (kgl & 7) * 32;
      d[0] = pack_bf16(h[0], h[1]);
      d[256] = pack_bf16(h[2], h[3]);
    }
    asm volatile("bar.arrive %0, 544;" ::"n"(NB_HID) : "memory");
  }
  if (tid == 0) TRACE(0, 6);
  {
    const float kmax2 = __uint_as_float(__reduce_max_sync(~0u, kmax_bits)), vmax = __uint_as_float(__reduce_max_sync(~0u, vmax_bits));
    const bool odd = hd & 1;
    const uint32_t kv0 = sd >> 4, bb = bar + B_KV;
    constexpr uint32_t TB = KV_TILE >> 4, VOFF = (6144 >> 4) + (24u << 16);
    constexpr uint32_t FREE_MASK = (1u << 2) | (1u << 4) | (1u << 6) | (1u << 9) | (1u << 11) | (1u << 13);
    uint32_t one2 = 0x3F803F80u;
    asm volatile("" : "+r"(one2));
    #pragma unroll 1
    for (int r = 0; r < 2; r++) {
      const int tg = qq * 64 + wg * 16 + r * 8 + w4 * 2;
      if (r == 1) load_q(tg);
      const bool real2 = odd ? (t >= 2) : (t < 2);
      float n0 = bf_lo(qa[0]) * bf_lo(qa[0]) + bf_hi(qa[0]) * bf_hi(qa[0]) + bf_lo(qa[2]) * bf_lo(qa[2]) + bf_hi(qa[2]) * bf_hi(qa[2]);
      float n1 = bf_lo(qa[1]) * bf_lo(qa[1]) + bf_hi(qa[1]) * bf_hi(qa[1]) + bf_lo(qa[3]) * bf_lo(qa[3]) + bf_hi(qa[3]) * bf_hi(qa[3]);
      if (real2) { n0 += bf_lo(qa[4]) * bf_lo(qa[4]) + bf_hi(qa[4]) * bf_hi(qa[4]); n1 += bf_lo(qa[5]) * bf_lo(qa[5]) + bf_hi(qa[5]) * bf_hi(qa[5]); }
      n0 += __shfl_xor_sync(~0u, n0, 1); n0 += __shfl_xor_sync(~0u, n0, 2);
      n1 += __shfl_xor_sync(~0u, n1, 1); n1 += __shfl_xor_sync(~0u, n1, 2);
      const bool ok = (n0 * kmax2 * 1.06f <= FAST_BOUND2) && (n1 * kmax2 * 1.06f <= FAST_BOUND2) && (vmax <= FAST_VMAX);
      int allok;
      asm volatile("{\n.reg .pred p, q;\nsetp.ne.b32 p, %1, 0;\nbarrier.red.and.pred q, %2, 128, p;\nselp.b32 %0, 1, 0, q;\n}" : "=r"(allok) : "r"((int)ok), "r"(NB_WG + wg) : "memory");
      allok = __shfl_sync(~0u, allok, 0);
      float o[12];
      #pragma unroll
      for (int i = 0; i < 12; i++) o[i] = 0.f;
      int freed = 0;
      if (allok) {
        float s0[32], s1[32]; uint32_t p[16];
        if (r == 0) mbar_wait(bb, 0);
        if (tid == 0) TRACE(1, 2 + r);
        wg_fence(); issue_qk(s0, qa, kv0); wg_commit(); wg_wait<0>();
        #pragma unroll 1
        for (int j = 0; j < 16; j++) {
          const uint32_t base = kv0 + j * TB;
          wg_fence(); issue_qk(s1, qa, base + 192u); wg_commit();
          exp_tile(s0, p, MUFU_MASK & 0xFF, one2);
          wg_fence(); issue_pv(o, p, base + VOFF); wg_commit();
          if (r == 0 && j < 15) mbar_wait(bb + (j + 1) * 8, 0);
          wg_wait<0>();
          wg_fence(); issue_qk(s0, qa, j < 15 ? base + TB : base); wg_commit();
          exp_tile(s1, p, MUFU_MASK >> 8, one2);
          wg_fence(); issue_pv(o, p, base + VOFF + 4 * 48u); wg_commit();
          wg_wait<0>();
          if (r == 1 && ((FREE_MASK >> j) & 1)) { if (lane < 2) mbar_arrive_cta(bar + B_KVFREE + 8 * freed, lane); freed++; }
        }
      } else {
        if (!real2) { qa[4] = 0; qa[5] = 0; }
        float m0 = -INFINITY, m1 = -INFINITY;
        float sc[32]; uint32_t p[16];
        #pragma unroll 1
        for (int u = 0; u < 32; u++) {
          const uint32_t base = kv0 + (u >> 1) * TB;
          mbar_wait(bb + (u >> 1) * 8, 0);
          wg_fence(); issue_qk(sc, qa, base + (u & 1) * 192u); wg_commit(); wg_wait<0>();
          float x0 = m0, x1 = m1;
          #pragma unroll
          for (int i = 0; i < 8; i++) { x0 = fmaxf(x0, fmaxf(sc[4 * i], sc[4 * i + 1])); x1 = fmaxf(x1, fmaxf(sc[4 * i + 2], sc[4 * i + 3])); }
          x0 = fmaxf(x0, __shfl_xor_sync(~0u, x0, 1)); x0 = fmaxf(x0, __shfl_xor_sync(~0u, x0, 2));
          x1 = fmaxf(x1, __shfl_xor_sync(~0u, x1, 1)); x1 = fmaxf(x1, __shfl_xor_sync(~0u, x1, 2));
          const float c0 = ex2(m0 - x0), c1 = ex2(m1 - x1);
          m0 = x0; m1 = x1;
          #pragma unroll
          for (int i = 0; i < 3; i++) { o[4 * i] *= c0; o[4 * i + 1] *= c0; o[4 * i + 2] *= c1; o[4 * i + 3] *= c1; }
          #pragma unroll
          for (int i = 0; i < 8; i++) {
            p[2 * i] = pack_bf16(ex2(sc[4 * i] - m0), ex2(sc[4 * i + 1] - m0));
            p[2 * i + 1] = pack_bf16(ex2(sc[4 * i + 2] - m1), ex2(sc[4 * i + 3] - m1));
          }
          wg_fence(); issue_pv(o, p, base + VOFF + (u & 1) * 4 * 48u); wg_commit(); wg_wait<0>();
        }
        if (r == 1 && lane < 2) for (int i = 0; i < 6; i++) mbar_arrive_cta(bar + B_KVFREE + 8 * i, lane);
      }
      const int src = (lane & ~3) | (odd ? 0 : 2);
      const float i0 = 1.f / __shfl_sync(~0u, o[8], src), i1 = 1.f / __shfl_sync(~0u, o[10], src);
      const int kg0 = (20 * hd) >> 3;
      uint32_t* ob = reinterpret_cast<uint32_t*>(g_att + ((size_t)(tg >> 4) * 10 * 16 + (tg & 15)) * 512) + lane;
      auto kaddr = [&](int kg) { return ob + (kg >> 3) * 4096 + (kg & 7) * 32; };
      uint32_t* d0 = kaddr(odd ? kg0 + 1 : kg0);
      uint32_t* d1 = kaddr(odd ? kg0 + 2 : kg0 + 1);
      uint32_t* d2 = kaddr(odd ? kg0 : kg0 + 2);
      d0[0] = pack_bf16(o[0] * i0, o[1] * i0); d0[256] = pack_bf16(o[2] * i1, o[3] * i1);
      d1[0] = pack_bf16(o[4] * i0, o[5] * i0); d1[256] = pack_bf16(o[6] * i1, o[7] * i1);
      if (real2) { d2[0] = pack_bf16(o[8] * i0, o[9] * i0); d2[256] = pack_bf16(o[10] * i1, o[11] * i1); }
    }
    asm volatile("bar.arrive %0, 544;" ::"n"(NB_ATT) : "memory");
  }
  if (tid == 0) TRACE(1, 4);
  if (wg < 2) {
    float acc[40];
    const int row0 = rbD * 128 + wg * 64 + w4 * 16;
    uint4 xv[5], bv[5];
    #pragma unroll
    for (int it = 0; it < 5; it++) {
      const int idx = it * 32 + lane, r = idx / 10, c8 = idx % 10;
      xv[it] = __ldg(reinterpret_cast<const uint4*>(x + (size_t)(row0 + r) * DM + cbD * 80 + c8 * 8));
      bv[it] = __ldg(reinterpret_cast<const uint4*>(b2 + cbD * 80 + c8 * 8));
    }
    int sD = 0; uint32_t phD = 0;
    #pragma unroll 1
    for (int kb = 0; kb < 34; kb++) {
      mbar_wait(bar + B_DFULL + 8 * sD, phD);
      if (tid == 0 && kb == 0) TRACE(2, 1);
      if (tid == 0 && kb == 24) TRACE(2, 2);
      const uint32_t alo = ((sd + sD * D_STAGE + wg * 8192) >> 4) | (8u << 16);
      const uint32_t blo = ((sd + sD * D_STAGE + 16384) >> 4) | (256u << 16);
      wg_fence();
      #pragma unroll
      for (int k = 0; k < 4; k++) wgmma_n80_ss(acc, alo + k * 16, 64u, blo + k * 64, 32u | (2u << 30), (kb | k) != 0);
      wg_commit();
      if (kb > 0) { wg_wait<1>(); if (lane < 2) mbar_arrive_cta(bar + B_DEMPTY + 8 * (sD == 0 ? 5 : sD - 1), lane); }
      if (++sD == 6) { sD = 0; phD ^= 1; }
    }
    wg_wait<0>();
    if (tid == 0) TRACE(2, 3);
    float* stg = reinterpret_cast<float*>(smem) + warp * (16 * 84);
    bar_sync(NB_FIN, 256);
    #pragma unroll
    for (int i = 0; i < 10; i++) {
      *reinterpret_cast<float2*>(stg + g * 84 + 8 * i + 2 * t) = make_float2(acc[4 * i], acc[4 * i + 1]);
      *reinterpret_cast<float2*>(stg + (g + 8) * 84 + 8 * i + 2 * t) = make_float2(acc[4 * i + 2], acc[4 * i + 3]);
    }
    __syncwarp();
    #pragma unroll
    for (int it = 0; it < 5; it++) {
      const int idx = it * 32 + lane, r = idx / 10, c8 = idx % 10;
      const size_t go = (size_t)(row0 + r) * DM + cbD * 80 + c8 * 8;
      const float4 a0 = *reinterpret_cast<const float4*>(stg + r * 84 + c8 * 8), a1 = *reinterpret_cast<const float4*>(stg + r * 84 + c8 * 8 + 4);
      uint4 o;
      o.x = pack_bf16(a0.x + bf_lo(bv[it].x) + bf_lo(xv[it].x), a0.y + bf_hi(bv[it].x) + bf_hi(xv[it].x));
      o.y = pack_bf16(a0.z + bf_lo(bv[it].y) + bf_lo(xv[it].y), a0.w + bf_hi(bv[it].y) + bf_hi(xv[it].y));
      o.z = pack_bf16(a1.x + bf_lo(bv[it].z) + bf_lo(xv[it].z), a1.y + bf_hi(bv[it].z) + bf_hi(xv[it].z));
      o.w = pack_bf16(a1.z + bf_lo(bv[it].w) + bf_lo(xv[it].w), a1.w + bf_hi(bv[it].w) + bf_hi(xv[it].w));
      *reinterpret_cast<uint4*>(out + go) = o;
    }
    if (tid == 0) TRACE(2, 4);
  }
  cluster_sync();
}

typedef CUresult (*EncodeTiledFn)(CUtensorMap*, CUtensorMapDataType, cuuint32_t, void*, const cuuint64_t*, const cuuint64_t*, const cuuint32_t*,
                                  const cuuint32_t*, CUtensorMapInterleave, CUtensorMapSwizzle, CUtensorMapL2promotion, CUtensorMapFloatOOBfill);

CUtensorMap make_map(EncodeTiledFn fn, const void* base, int rank, const cuuint64_t* dims, const cuuint64_t* strides, const cuuint32_t* box, CUtensorMapSwizzle sw) {
  CUtensorMap m;
  const cuuint32_t es[3] = {1, 1, 1};
  CUresult rc = fn(&m, CU_TENSOR_MAP_DATA_TYPE_BFLOAT16, rank, const_cast<void*>(base), dims, strides, box, es, CU_TENSOR_MAP_INTERLEAVE_NONE, sw,
                   CU_TENSOR_MAP_L2_PROMOTION_L2_128B, CU_TENSOR_MAP_FLOAT_OOB_FILL_NONE);
  (void)rc;
  return m;
}

}

extern "C" void kernel_launch(void* const* d_in, const int* in_sizes, int n_in, void* d_out, int out_size) {
  const __nv_bfloat16* x = static_cast<const __nv_bfloat16*>(d_in[0]);
  const __nv_bfloat16* wqkv = static_cast<const __nv_bfloat16*>(d_in[1]);
  const __nv_bfloat16* wo = static_cast<const __nv_bfloat16*>(d_in[2]);
  const __nv_bfloat16* w1 = static_cast<const __nv_bfloat16*>(d_in[4]);
  const __nv_bfloat16* b1 = static_cast<const __nv_bfloat16*>(d_in[5]);
  const __nv_bfloat16* w2 = static_cast<const __nv_bfloat16*>(d_in[6]);
  const __nv_bfloat16* b2 = static_cast<const __nv_bfloat16*>(d_in[7]);
  __nv_bfloat16* out = static_cast<__nv_bfloat16*>(d_out);

  static EncodeTiledFn encode = nullptr;
  if (!encode) {
    void* fn = nullptr;
    cudaDriverEntryPointQueryResult qr;
    cudaGetDriverEntryPoint("cuTensorMapEncodeTiled", &fn, cudaEnableDefault, &qr);
    encode = reinterpret_cast<EncodeTiledFn>(fn);
    cudaFuncSetAttribute(fused_block, cudaFuncAttributeMaxDynamicSharedMemorySize, SMEM_BYTES);
  }
  Maps tm;
  { const cuuint64_t d[2] = {DM, S_LEN}, st[1] = {DM * 2}; const cuuint32_t b[2] = {64, 128}; tm.x = make_map(encode, x, 2, d, st, b, CU_TENSOR_MAP_SWIZZLE_128B); }
  { const cuuint64_t d[2] = {NQKV, DM}, st[1] = {NQKV * 2}; const cuuint32_t b[2] = {64, 32}; tm.wqkv = make_map(encode, wqkv, 2, d, st, b, CU_TENSOR_MAP_SWIZZLE_128B); }
  { const cuuint64_t d[3] = {32, DM, FF / 32}, st[2] = {FF * 2, 64}; const cuuint32_t b[3] = {32, 32, 6}; tm.w1 = make_map(encode, w1, 3, d, st, b, CU_TENSOR_MAP_SWIZZLE_64B); }
  { const cuuint64_t d[2] = {NQKV, DM}, st[1] = {NQKV * 2}; const cuuint32_t b[2] = {16, 160}; tm.sq = make_map(encode, wqkv, 2, d, st, b, CU_TENSOR_MAP_SWIZZLE_NONE); }
  { const cuuint64_t d[2] = {FF, DM}, st[1] = {FF * 2}; const cuuint32_t b[2] = {16, 160}; tm.s1 = make_map(encode, w1, 2, d, st, b, CU_TENSOR_MAP_SWIZZLE_NONE); }
  { const cuuint64_t d[2] = {DM, FF}, st[1] = {DM * 2}; const cuuint32_t b[2] = {32, 64}; tm.w2 = make_map(encode, w2, 2, d, st, b, CU_TENSOR_MAP_SWIZZLE_64B); }
  { const cuuint64_t d[2] = {DM, DM}, st[1] = {DM * 2}; const cuuint32_t b[2] = {32, 64}; tm.wo = make_map(encode, wo, 2, d, st, b, CU_TENSOR_MAP_SWIZZLE_64B); }

  cudaLaunchAttribute at[1];
  at[0].id = cudaLaunchAttributeClusterDimension; at[0].val.clusterDim.x = 2; at[0].val.clusterDim.y = 1; at[0].val.clusterDim.z = 1;
  cudaLaunchConfig_t cfg = {};
  cfg.stream = cudaStreamPerThread;
  cfg.gridDim = dim3(128); cfg.blockDim = dim3(640); cfg.dynamicSmemBytes = SMEM_BYTES; cfg.attrs = at; cfg.numAttrs = 1;
  cudaLaunchKernelEx(&cfg, fused_block, tm, x, b1, w2, wo, b2, out);
}
```

```cpp
#include <cuda_runtime.h>
#include <cuda_bf16.h>
#include <cuda.h>
#include <stdint.h>

namespace {

constexpr int S_LEN = 2048, DM = 640, NH = 32, FF = 1536, NQKV = 1920;
constexpr float LN_EPS = 1e-5f;

__device__ __align__(1024) __nv_bfloat16 g_qkv[3 * NH * 256 * 192];
__device__ __align__(1024) __nv_bfloat16 g_hid[16 * 24 * 8192];
__device__ __align__(1024) __nv_bfloat16 g_att[16 * 10 * 8192];
__device__ float2 g_rowstat[2 * S_LEN];
__device__ float2 g_colsum[NQKV + FF];
__device__ float g_knorm[NH * 128];
__device__ float g_vmax[NH * 128];
__device__ unsigned g_epoch;
__device__ unsigned g_cnt[6 * 32];

#define TRACE(k, i)

__device__ __forceinline__ uint32_t smem_u32(const void* p) { return (uint32_t)__cvta_generic_to_shared(p); }
__device__ __forceinline__ void wg_fence() { asm volatile("wgmma.fence.sync.aligned;" ::: "memory"); }
__device__ __forceinline__ void wg_commit() { asm volatile("wgmma.commit_group.sync.aligned;" ::: "memory"); }
template <int N> __device__ __forceinline__ void wg_wait() { asm volatile("wgmma.wait_group.sync.aligned %0;" ::"n"(N) : "memory"); }
__device__ __forceinline__ void mbar_init(uint32_t bar, int cnt) { asm volatile("mbarrier.init.shared::cta.b64 [%0], %1;" ::"r"(bar), "r"(cnt)); }
__device__ __forceinline__ void mbar_expect(uint32_t bar, uint32_t bytes) {
  asm volatile("mbarrier.arrive.expect_tx.shared::cta.b64 _, [%0], %1;" ::"r"(bar), "r"(bytes) : "memory");
}
__device__ __forceinline__ void mbar_expect_only(uint32_t bar, uint32_t bytes) {
  asm volatile("mbarrier.expect_tx.relaxed.cta.shared::cta.b64 [%0], %1;" ::"r"(bar), "r"(bytes) : "memory");
}
__device__ __forceinline__ void mbar_arrive(uint32_t bar) { asm volatile("mbarrier.arrive.shared::cta.b64 _, [%0];" ::"r"(bar) : "memory"); }
__device__ __forceinline__ void mbar_arrive_cta(uint32_t bar, uint32_t cta) {
  asm volatile("{\n.reg .b32 r;\nmapa.shared::cluster.u32 r, %0, %1;\nmbarrier.arrive.shared::cluster.b64 _, [r];\n}" ::"r"(bar), "r"(cta) : "memory");
}
__device__ __forceinline__ void mbar_wait(uint32_t bar, uint32_t parity) {
  asm volatile("{\n.reg .pred p;\nWAIT:\nmbarrier.try_wait.parity.shared::cta.b64 p, [%0], %1;\n@p bra DONE;\nbra WAIT;\nDONE:\n}" ::"r"(bar), "r"(parity) : "memory");
}
__device__ __forceinline__ void bulk_load(uint32_t dst, const void* src, uint32_t bytes, uint32_t bar) {
  asm volatile("cp.async.bulk.shared::cluster.global.mbarrier::complete_tx::bytes [%0], [%1], %2, [%3];" ::"r"(dst), "l"(src), "r"(bytes), "r"(bar) : "memory");
}
__device__ __forceinline__ void tma_2d(uint32_t dst, const CUtensorMap* tm, int c0, int c1, uint32_t bar) {
  asm volatile("cp.async.bulk.tensor.2d.shared::cluster.global.mbarrier::complete_tx::bytes [%0], [%1, {%3, %4}], [%2];" ::"r"(dst), "l"(tm), "r"(bar), "r"(c0), "r"(c1) : "memory");
}
__device__ __forceinline__ void tma_2d_mc(uint32_t dst, const CUtensorMap* tm, int c0, int c1, uint32_t bar, uint16_t mask) {
  asm volatile("cp.async.bulk.tensor.2d.shared::cluster.global.mbarrier::complete_tx::bytes.multicast::cluster [%0], [%1, {%3, %4}], [%2], %5;" ::"r"(dst), "l"(tm), "r"(bar), "r"(c0), "r"(c1), "h"(mask) : "memory");
}
__device__ __forceinline__ void tma_3d_mc(uint32_t dst, const CUtensorMap* tm, int c0, int c1, int c2, uint32_t bar, uint16_t mask) {
  asm volatile("cp.async.bulk.tensor.3d.shared::cluster.global.mbarrier::complete_tx::bytes.multicast::cluster [%0], [%1, {%3, %4, %5}], [%2], %6;" ::"r"(dst), "l"(tm), "r"(bar), "r"(c0), "r"(c1), "r"(c2), "h"(mask) : "memory");
}
__device__ __forceinline__ void tma_4d_mc(uint32_t dst, const CUtensorMap* tm, int c0, int c1, int c2, int c3, uint32_t bar, uint16_t mask) {
  asm volatile("cp.async.bulk.tensor.4d.shared::cluster.global.mbarrier::complete_tx::bytes.multicast::cluster [%0], [%1, {%3, %4, %5, %6}], [%2], %7;" ::"r"(dst), "l"(tm), "r"(bar), "r"(c0), "r"(c1), "r"(c2), "r"(c3), "h"(mask) : "memory");
}
__device__ __forceinline__ void cluster_sync() { asm volatile("barrier.cluster.arrive.relaxed.aligned;\nbarrier.cluster.wait.aligned;" ::: "memory"); }
__device__ __forceinline__ void bar_sync(int id, int n) { asm volatile("bar.sync %0, %1;" ::"r"(id), "r"(n) : "memory"); }
__device__ __forceinline__ float ex2(float x) { float y; asm("ex2.approx.ftz.f32 %0, %1;" : "=f"(y) : "f"(x)); return y; }
__device__ __forceinline__ float tanh_fast(float x) { float y; asm("tanh.approx.f32 %0, %1;" : "=f"(y) : "f"(x)); return y; }
__device__ __forceinline__ uint32_t pack_bf16(float lo, float hi) { uint32_t r; asm("cvt.rn.bf16x2.f32 %0, %1, %2;" : "=r"(r) : "f"(hi), "f"(lo)); return r; }
__device__ __forceinline__ uint32_t hfma2_bf16(uint32_t a, uint32_t b, uint32_t c) { uint32_t r; asm("fma.rn.bf16x2 %0, %1, %2, %3;" : "=r"(r) : "r"(a), "r"(b), "r"(c)); return r; }
__device__ __forceinline__ uint32_t hmul2_bf16(uint32_t a, uint32_t b) { uint32_t r; asm("mul.rn.bf16x2 %0, %1, %2;" : "=r"(r) : "r"(a), "r"(b)); return r; }
template <int LUT> __device__ __forceinline__ uint32_t lop3(uint32_t a, uint32_t b, uint32_t c) {
  uint32_t r; asm("lop3.b32 %0, %1, %2, %3, %4;" : "=r"(r) : "r"(a), "r"(b), "r"(c), "n"(LUT)); return r;
}
__device__ __forceinline__ float bf_lo(uint32_t v) { return __uint_as_float(v << 16); }
__device__ __forceinline__ float bf_hi(uint32_t v) { return __uint_as_float(v & 0xFFFF0000u); }

__device__ __forceinline__ void wgmma_n120_ss(float (&d)[60], uint32_t alo, uint32_t ahi, uint32_t blo, uint32_t bhi, int scaleD) {
  asm volatile("{\n.reg .pred p;\n.reg .b64 da, db;\nsetp.ne.b32 p, %64, 0;\nmov.b64 da, {%60, %61};\nmov.b64 db, {%62, %63};\n"
    "wgmma.mma_async.sync.aligned.m64n120k16.f32.bf16.bf16 "
    "{%0,%1,%2,%3,%4,%5,%6,%7,%8,%9,%10,%11,%12,%13,%14,%15,%16,%17,%18,%19,%20,%21,%22,%23,%24,%25,%26,%27,%28,%29,%30,%31,%32,%33,%34,%35,%36,%37,%38,%39,%40,%41,%42,%43,%44,%45,%46,%47,%48,%49,%50,%51,%52,%53,%54,%55,%56,%57,%58,%59}, "
    "da, db, p, 1, 1, 0, 1;\n}\n"
    :
      "+f"(d[0]), "+f"(d[1]), "+f"(d[2]), "+f"(d[3]), "+f"(d[4]), "+f"(d[5]), "+f"(d[6]), "+f"(d[7]),
      "+f"(d[8]), "+f"(d[9]), "+f"(d[10]), "+f"(d[11]), "+f"(d[12]), "+f"(d[13]), "+f"(d[14]), "+f"(d[15]),
      "+f"(d[16]), "+f"(d[17]), "+f"(d[18]), "+f"(d[19]), "+f"(d[20]), "+f"(d[21]), "+f"(d[22]), "+f"(d[23]),
      "+f"(d[24]), "+f"(d[25]), "+f"(d[26]), "+f"(d[27]), "+f"(d[28]), "+f"(d[29]), "+f"(d[30]), "+f"(d[31]),
      "+f"(d[32]), "+f"(d[33]), "+f"(d[34]), "+f"(d[35]), "+f"(d[36]), "+f"(d[37]), "+f"(d[38]), "+f"(d[39]),
      "+f"(d[40]), "+f"(d[41]), "+f"(d[42]), "+f"(d[43]), "+f"(d[44]), "+f"(d[45]), "+f"(d[46]), "+f"(d[47]),
      "+f"(d[48]), "+f"(d[49]), "+f"(d[50]), "+f"(d[51]), "+f"(d[52]), "+f"(d[53]), "+f"(d[54]), "+f"(d[55]),
      "+f"(d[56]), "+f"(d[57]), "+f"(d[58]), "+f"(d[59])
    : "r"(alo), "r"(ahi), "r"(blo), "r"(bhi), "r"(scaleD));
}
__device__ __forceinline__ void wgmma_n96_ss(float (&d)[48], uint32_t alo, uint32_t ahi, uint32_t blo, uint32_t bhi, int scaleD) {
  asm volatile("{\n.reg .pred p;\n.reg .b64 da, db;\nsetp.ne.b32 p, %52, 0;\nmov.b64 da, {%48, %49};\nmov.b64 db, {%50, %51};\n"
    "wgmma.mma_async.sync.aligned.m64n96k16.f32.bf16.bf16 "
    "{%0,%1,%2,%3,%4,%5,%6,%7,%8,%9,%10,%11,%12,%13,%14,%15,%16,%17,%18,%19,%20,%21,%22,%23,%24,%25,%26,%27,%28,%29,%30,%31,%32,%33,%34,%35,%36,%37,%38,%39,%40,%41,%42,%43,%44,%45,%46,%47}, "
    "da, db, p, 1, 1, 0, 1;\n}\n"
    :
      "+f"(d[0]), "+f"(d[1]), "+f"(d[2]), "+f"(d[3]), "+f"(d[4]), "+f"(d[5]), "+f"(d[6]), "+f"(d[7]),
      "+f"(d[8]), "+f"(d[9]), "+f"(d[10]), "+f"(d[11]), "+f"(d[12]), "+f"(d[13]), "+f"(d[14]), "+f"(d[15]),
      "+f"(d[16]), "+f"(d[17]), "+f"(d[18]), "+f"(d[19]), "+f"(d[20]), "+f"(d[21]), "+f"(d[22]), "+f"(d[23]),
      "+f"(d[24]), "+f"(d[25]), "+f"(d[26]), "+f"(d[27]), "+f"(d[28]), "+f"(d[29]), "+f"(d[30]), "+f"(d[31]),
      "+f"(d[32]), "+f"(d[33]), "+f"(d[34]), "+f"(d[35]), "+f"(d[36]), "+f"(d[37]), "+f"(d[38]), "+f"(d[39]),
      "+f"(d[40]), "+f"(d[41]), "+f"(d[42]), "+f"(d[43]), "+f"(d[44]), "+f"(d[45]), "+f"(d[46]), "+f"(d[47])
    : "r"(alo), "r"(ahi), "r"(blo), "r"(bhi), "r"(scaleD));
}
__device__ __forceinline__ void wgmma_n64_ss(float (&d)[32], uint32_t alo, uint32_t ahi, uint32_t blo, uint32_t bhi, int scaleD) {
  asm volatile("{\n.reg .pred p;\n.reg .b64 da, db;\nsetp.ne.b32 p, %36, 0;\nmov.b64 da, {%32, %33};\nmov.b64 db, {%34, %35};\n"
    "wgmma.mma_async.sync.aligned.m64n64k16.f32.bf16.bf16 "
    "{%0,%1,%2,%3,%4,%5,%6,%7,%8,%9,%10,%11,%12,%13,%14,%15,%16,%17,%18,%19,%20,%21,%22,%23,%24,%25,%26,%27,%28,%29,%30,%31}, "
    "da, db, p, 1, 1, 0, 1;\n}\n"
    :
      "+f"(d[0]), "+f"(d[1]), "+f"(d[2]), "+f"(d[3]), "+f"(d[4]), "+f"(d[5]), "+f"(d[6]), "+f"(d[7]),
      "+f"(d[8]), "+f"(d[9]), "+f"(d[10]), "+f"(d[11]), "+f"(d[12]), "+f"(d[13]), "+f"(d[14]), "+f"(d[15]),
      "+f"(d[16]), "+f"(d[17]), "+f"(d[18]), "+f"(d[19]), "+f"(d[20]), "+f"(d[21]), "+f"(d[22]), "+f"(d[23]),
      "+f"(d[24]), "+f"(d[25]), "+f"(d[26]), "+f"(d[27]), "+f"(d[28]), "+f"(d[29]), "+f"(d[30]), "+f"(d[31])
    : "r"(alo), "r"(ahi), "r"(blo), "r"(bhi), "r"(scaleD));
}
__device__ __forceinline__ void wgmma_n64_rs(float (&d)[32], uint32_t a0, uint32_t a1, uint32_t a2, uint32_t a3, uint32_t blo, uint32_t bhi, int scaleD) {
  asm volatile("{\n.reg .pred p;\n.reg .b64 db;\nsetp.ne.b32 p, %38, 0;\nmov.b64 db, {%36, %37};\n"
    "wgmma.mma_async.sync.aligned.m64n64k16.f32.bf16.bf16 "
    "{%0,%1,%2,%3,%4,%5,%6,%7,%8,%9,%10,%11,%12,%13,%14,%15,%16,%17,%18,%19,%20,%21,%22,%23,%24,%25,%26,%27,%28,%29,%30,%31}, "
    "{%32, %33, %34, %35}, db, p, 1, 1, 0;\n}\n"
    :
      "+f"(d[0]), "+f"(d[1]), "+f"(d[2]), "+f"(d[3]), "+f"(d[4]), "+f"(d[5]), "+f"(d[6]), "+f"(d[7]),
      "+f"(d[8]), "+f"(d[9]), "+f"(d[10]), "+f"(d[11]), "+f"(d[12]), "+f"(d[13]), "+f"(d[14]), "+f"(d[15]),
      "+f"(d[16]), "+f"(d[17]), "+f"(d[18]), "+f"(d[19]), "+f"(d[20]), "+f"(d[21]), "+f"(d[22]), "+f"(d[23]),
      "+f"(d[24]), "+f"(d[25]), "+f"(d[26]), "+f"(d[27]), "+f"(d[28]), "+f"(d[29]), "+f"(d[30]), "+f"(d[31])
    : "r"(a0), "r"(a1), "r"(a2), "r"(a3), "r"(blo), "r"(bhi), "r"(scaleD));
}
__device__ __forceinline__ void wgmma_n24_rs(float (&d)[12], uint32_t a0, uint32_t a1, uint32_t a2, uint32_t a3, uint32_t blo, uint32_t bhi, int scaleD) {
  asm volatile("{\n.reg .pred p;\n.reg .b64 db;\nsetp.ne.b32 p, %18, 0;\nmov.b64 db, {%16, %17};\n"
    "wgmma.mma_async.sync.aligned.m64n24k16.f32.bf16.bf16 "
    "{%0,%1,%2,%3,%4,%5,%6,%7,%8,%9,%10,%11}, "
    "{%12, %13, %14, %15}, db, p, 1, 1, 1;\n}\n"
    :
      "+f"(d[0]), "+f"(d[1]), "+f"(d[2]), "+f"(d[3]), "+f"(d[4]), "+f"(d[5]), "+f"(d[6]), "+f"(d[7]),
      "+f"(d[8]), "+f"(d[9]), "+f"(d[10]), "+f"(d[11])
    : "r"(a0), "r"(a1), "r"(a2), "r"(a3), "r"(blo), "r"(bhi), "r"(scaleD));
}

#define MUFU_MASK_V 0x4949
constexpr uint32_t MUFU_MASK = MUFU_MASK_V;
constexpr float QSCALE = 0.22360679774997896f * 1.4426950408889634f;
constexpr float FAST_BOUND2 = 8100.f;
constexpr float FAST_VMAX = 1.0e6f;

#define SLAB_A_AT 1
#define SLAB_B_AT 8
#define LAG_A 99
#define H_STAGE 0
#define PF_AT 0
#define PF1_AT -1
#define ENTRY_PF 0
#define ROT_D 0
#define L2PROMO CU_TENSOR_MAP_L2_PROMOTION_L2_128B
#define KEEP_ZERO 1
#define EARLY_X 0
constexpr int AB_STAGE = 49152;
constexpr int KV_TILE = 12288;
constexpr int D_STAGE = 28672;
constexpr int SM_SLAB = 196608;
constexpr int SM_PARAM = SM_SLAB + 20480;
constexpr int SM_RED = SM_PARAM + 4608;
constexpr int SM_BARS = SM_RED + 512;
constexpr int SMEM_BYTES = SM_BARS + 512;
constexpr int B_FULL = 0, B_EMPTY = 32, B_PREADY = 64, B_SLAB = 80, B_SLABFREE = 96, B_QKV = 104, B_KV = 112, B_KVFREE = 240, B_DFULL = 288, B_DEMPTY = 336, B_HFREE = 384;
constexpr int NB_WG = 1, NB_QKV = 6, NB_HID = 7, NB_ATT = 8, NB_HELP = 9, NB_FIN = 10, NB_LAG = 11, NB_STG = 12;

__device__ __forceinline__ void st_tagged(float2* p, float v, float tag) {
  asm volatile("{\n.reg .b64 v;\nmov.b64 v, {%1, %2};\nst.relaxed.gpu.global.b64 [%0], v;\n}" ::"l"(p), "f"(v), "f"(tag) : "memory");
}
__device__ __forceinline__ bool ld_tagged(const float2* p, float& v, float tag) {
  float tg;
  asm volatile("{\n.reg .b64 v;\nld.relaxed.gpu.global.b64 v, [%2];\nmov.b64 {%0, %1}, v;\n}" : "=f"(v), "=f"(tg) : "l"(p) : "memory");
  return __float_as_uint(tg) == __float_as_uint(tag);
}
__device__ __forceinline__ void wait_counter(const unsigned* cnt, unsigned target) {
  unsigned cur; int spins = 0;
  do { asm volatile("ld.acquire.gpu.global.u32 %0, [%1];" : "=r"(cur) : "l"(cnt) : "memory"); } while ((int)(cur - target) < 0 && ++spins < (1 << 22));
  asm volatile("fence.proxy.async.global;" ::: "memory");
}

__device__ __forceinline__ uint32_t exp2_pair(float ta, float tb, uint32_t one2) {
  const uint32_t v = __byte_perm(__float_as_uint(ta), __float_as_uint(tb), 0x6521);
  const uint32_t m = lop3<0xEA>(v, 0x007F007Fu, one2);
  const uint32_t q = hfma2_bf16(m, 0xBDF4BDF4u, 0x3EB43EB4u);
  const uint32_t p = hfma2_bf16(q, m, 0xBF3BBF3Bu);
  return hmul2_bf16(v, p);
}
__device__ __forceinline__ void exp_tile(const float (&s)[32], uint32_t (&p)[16], const uint32_t mask, uint32_t one2) {
  #pragma unroll
  for (int i = 0; i < 8; i++) {
    if ((mask >> i) & 1) {
      p[2 * i] = pack_bf16(ex2(s[4 * i]), ex2(s[4 * i + 1]));
      p[2 * i + 1] = pack_bf16(ex2(s[4 * i + 2]), ex2(s[4 * i + 3]));
    } else {
      p[2 * i] = exp2_pair(s[4 * i], s[4 * i + 1], one2);
      p[2 * i + 1] = exp2_pair(s[4 * i + 2], s[4 * i + 3], one2);
    }
  }
}
__device__ __forceinline__ void issue_qk(float (&s)[32], const uint32_t (&qa)[8], uint32_t klo) {
  wgmma_n64_rs(s, qa[0], qa[1], qa[2], qa[3], klo | (8u << 16), 24u, 0);
  wgmma_n64_rs(s, qa[4], qa[5], qa[6], qa[7], klo + 16u, 24u, 1);
}
__device__ __forceinline__ void issue_pv(float (&o)[12], const uint32_t (&p)[16], uint32_t vlo) {
  #pragma unroll
  for (int kk = 0; kk < 4; kk++) wgmma_n24_rs(o, p[4 * kk], p[4 * kk + 1], p[4 * kk + 2], p[4 * kk + 3], vlo + kk * 48u, 8u, 1);
}

template <int V> struct IntC { static constexpr int value = V; };
struct Maps { CUtensorMap x, wqkv, wq4, w1, sq, s1, w2, wo; };

__global__ void __launch_bounds__(640, 1)
fused_block(const __grid_constant__ Maps tm, const __nv_bfloat16* __restrict__ x, const __nv_bfloat16* __restrict__ wqkv,
            const __nv_bfloat16* __restrict__ w1, const __nv_bfloat16* __restrict__ b1,
            const __nv_bfloat16* __restrict__ w2, const __nv_bfloat16* __restrict__ wo, const __nv_bfloat16* __restrict__ b2,
            __nv_bfloat16* __restrict__ out) {
  extern __shared__ __align__(1024) uint8_t smem[];
  const uint32_t sb = smem_u32(smem);
  const uint32_t sd = sb & 0x3FFFF;
  const uint32_t bar = sb + SM_BARS;
  float* s_cs = reinterpret_cast<float*>(smem + SM_PARAM);
  float* s_cs1 = s_cs + 240;
  float* s_b1h = s_cs1 + 192;
  float4* s_row = reinterpret_cast<float4*>(smem + SM_PARAM + 2560);
  const int tid = threadIdx.x, lane = tid & 31;
  const int warp = __shfl_sync(~0u, tid >> 5, 0), wg = warp >> 2;
  const int bid = blockIdx.x, rank = bid & 1;
  const int cbA = (bid >> 1) & 7, rbA = ((bid >> 4) << 1) | rank;
  const int hd = bid >> 2, qq = bid & 3;
  const int rbD = ((bid >> 3) << 1) | rank, cbD = (bid >> 1) & 3;

  if (tid == 0) TRACE(0, 0);
  if (tid == 0) {
    for (int s = 0; s < 4; s++) { mbar_init(bar + B_FULL + 8 * s, 1); mbar_init(bar + B_EMPTY + 8 * s, 32); }
    mbar_init(bar + B_PREADY, 64); mbar_init(bar + B_PREADY + 8, 64); mbar_init(bar + B_SLAB, 1); mbar_init(bar + B_SLAB + 8, 1);
    mbar_init(bar + B_SLABFREE, 64); mbar_init(bar + B_QKV, 1); mbar_init(bar + B_HFREE, 1);
    for (int j = 0; j < 16; j++) mbar_init(bar + B_KV + 8 * j, 1);
    for (int s = 0; s < 6; s++) { mbar_init(bar + B_KVFREE + 8 * s, 32); mbar_init(bar + B_DFULL + 8 * s, 1); mbar_init(bar + B_DEMPTY + 8 * s, 16); }
    asm volatile("fence.mbarrier_init.release.cluster;" ::: "memory");
  }
  if (tid == 512) {
    asm volatile("prefetch.tensormap [%0];" ::"l"(&tm.x) : "memory");
    asm volatile("prefetch.tensormap [%0];" ::"l"(cbA < 7 ? &tm.wq4 : &tm.wqkv) : "memory");
    asm volatile("prefetch.tensormap [%0];" ::"l"(&tm.sq) : "memory");
  }
  __syncthreads();
  if (tid == 0) TRACE(0, 12);
  cluster_sync();
  if (tid == 0) TRACE(0, 13);

  if (wg == 4) {
    asm volatile("setmaxnreg.dec.sync.aligned.u32 32;");
    if (warp == 16) {
      if (lane == 0) {
        int s = 0; uint32_t ph = 1;
        const unsigned epoch_prev = __ldcg(&g_epoch);
        #pragma unroll 1
        for (int it = 0; it < 20; it++) {
          const int kb = it < 10 ? it : (it < 14 ? it - 4 : it - 14);
          mbar_wait(bar + B_EMPTY + 8 * s, ph);
          const uint32_t sa = sb + s * AB_STAGE, sw = sa + 16384, fb = bar + B_FULL + 8 * s;
          if (it < 10) {
            if (it == 0) TRACE(0, 11);
            mbar_expect(fb, it < EARLY_X ? 32768 : 16384 + 32768);
            if (it >= EARLY_X) tma_2d(sa, &tm.x, kb * 64, rbA * 128, fb);
            if (cbA < 7) tma_4d_mc(sw + rank * 16384, &tm.wq4, 0, kb * 64 + rank * 32, 0, cbA * 2, fb, 3);
            else for (int b = 0; b < 4; b++) tma_2d_mc(sw + rank * 16384 + b * 4096, &tm.wqkv, cbA * 240 + b * 64 - (b >> 1) * 8, kb * 64 + rank * 32, fb, 3);
          } else {
            mbar_expect(fb, it < 14 ? 24576 : 16384 + 24576);
            if (it >= 14) tma_2d(sa, &tm.x, kb * 64, rbA * 128, fb);
            tma_3d_mc(sw + rank * 12288, &tm.w1, 0, kb * 64 + rank * 32, cbA * 6, fb, 3);
          }
          if (PF_AT >= 0 && it == PF_AT) {
            asm volatile("cp.async.bulk.prefetch.L2.global [%0], %1;" ::"l"((const uint8_t*)x + (size_t)bid * (S_LEN * DM * 2 / 128)), "r"(S_LEN * DM * 2 / 128) : "memory");
            asm volatile("cp.async.bulk.prefetch.L2.global [%0], %1;" ::"l"((const uint8_t*)wqkv + (size_t)bid * (DM * NQKV * 2 / 128)), "r"(DM * NQKV * 2 / 128) : "memory");
          }
          if (PF1_AT >= 0 && it == PF1_AT)
            asm volatile("cp.async.bulk.prefetch.L2.global [%0], %1;" ::"l"((const uint8_t*)w1 + (size_t)bid * (DM * FF * 2 / 128)), "r"(DM * FF * 2 / 128) : "memory");
          if (it == SLAB_A_AT && bid < 120) {
            mbar_expect(bar + B_SLAB, 20480);
            for (int i = 0; i < 4; i++) tma_2d(sb + SM_SLAB + i * 5120, &tm.sq, bid * 16, i * 160, bar + B_SLAB);
          }
          if (it == SLAB_B_AT && bid < 96) {
            mbar_wait(bar + B_SLABFREE, 0);
            mbar_expect(bar + B_SLAB + 8, 20480);
            for (int i = 0; i < 4; i++) tma_2d(sb + SM_SLAB + i * 5120, &tm.s1, bid * 16, i * 160, bar + B_SLAB + 8);
          }
          if (++s == 4) { s = 0; ph ^= 1; }
        }
        const unsigned epoch = epoch_prev + 1u;
        wait_counter(&g_cnt[0], epoch * 128u);
        mbar_arrive(bar + B_QKV);
        const uint8_t* ksrc = reinterpret_cast<const uint8_t*>(g_qkv + (size_t)(NH + hd) * 256 * 192);
        const uint8_t* vsrc = reinterpret_cast<const uint8_t*>(g_qkv + (size_t)(2 * NH + hd) * 256 * 192);
        #pragma unroll 1
        for (int j = 0; j < 16; j++) {
          if ((j & 3) == 0) mbar_wait(bar + B_EMPTY + 8 * (j >> 2), ph);
          if (H_STAGE && j == 12) mbar_wait(bar + B_HFREE, 0);
          mbar_expect(bar + B_KV + 8 * j, KV_TILE);
          bulk_load(sb + j * KV_TILE, ksrc + j * 6144, 6144, bar + B_KV + 8 * j);
          bulk_load(sb + j * KV_TILE + 6144, vsrc + j * 6144, 6144, bar + B_KV + 8 * j);
        }
        if (tid == 512) TRACE(0, 9);
        asm volatile("cp.async.bulk.prefetch.L2.global [%0], %1;" ::"l"((const uint8_t*)w2 + (size_t)bid * (FF * DM * 2 / 128)), "r"(FF * DM * 2 / 128) : "memory");
        asm volatile("cp.async.bulk.prefetch.L2.global [%0], %1;" ::"l"((const uint8_t*)wo + (size_t)bid * (DM * DM * 2 / 128)), "r"(DM * DM * 2 / 128) : "memory");
        wait_counter(&g_cnt[32], epoch * 128u);
        s = 0; ph = 1;
        #pragma unroll 1
        for (int kb = 0; kb < 34; kb++) {
          if (kb == 24) {
            wait_counter(&g_cnt[64 + 32 * (rbD >> 3)], epoch * 32u);
            if (bid == 0) g_epoch = epoch;
          }
          if (kb < 6) mbar_wait(bar + B_KVFREE + 8 * s, 0); else mbar_wait(bar + B_DEMPTY + 8 * s, ph);
          const uint32_t sa = sb + s * D_STAGE, fb = bar + B_DFULL + 8 * s;
          mbar_expect(fb, D_STAGE);
          int kk = kb < 24 ? kb + ROT_D * (bid >> 3) : kb - 24 + ROT_D * (bid >> 3);
          kk = kb < 24 ? kk % 24 : kk % 10;
          const __nv_bfloat16* asrc = (kb < 24 ? g_hid + (size_t)((rbD >> 1) * 24 + kk) * 8192 : g_att + (size_t)((rbD >> 1) * 10 + kk) * 8192) + (rbD & 1) * 4096;
          bulk_load(sa, asrc, 8192, fb);
          tma_3d_mc(sa + 8192 + rank * 10240, kb < 24 ? &tm.w2 : &tm.wo, 0, kk * 64 + rank * 32, cbD * 5, fb, 3);
          if (++s == 6) { s = 0; ph ^= 1; }
        }
      }
    } else {
      if (warp == 19) {
        bar_sync(NB_QKV, 544);
        if (lane == 0) { __threadfence(); atomicAdd(&g_cnt[0], 1u); }
        __syncwarp();
        bar_sync(NB_HID, 544);
        if (lane == 0) { __threadfence(); atomicAdd(&g_cnt[32], 1u); }
        __syncwarp();
        bar_sync(NB_ATT, 544);
        if (lane == 0) { __threadfence(); atomicAdd(&g_cnt[64 + 32 * qq], 1u); }
        __syncwarp();
      } else {
        const int w = warp - 17, t64 = tid - 544;
        const float tag = __uint_as_float(__ldcg(&g_epoch) + 1u);
        float* s_red = reinterpret_cast<float*>(smem + SM_RED);
        auto slab_sum = [&](uint32_t fullbar, float2* dst) {
          mbar_wait(fullbar, 0);
          float a[8];
          #pragma unroll
          for (int i = 0; i < 8; i++) a[i] = 0.f;
          #pragma unroll 2
          for (int i = w; i < 40; i += 2) {
            const uint4 u = *reinterpret_cast<const uint4*>(smem + SM_SLAB + i * 512 + lane * 16);
            a[0] += bf_lo(u.x); a[1] += bf_hi(u.x); a[2] += bf_lo(u.y); a[3] += bf_hi(u.y);
            a[4] += bf_lo(u.z); a[5] += bf_hi(u.z); a[6] += bf_lo(u.w); a[7] += bf_hi(u.w);
          }
          #pragma unroll
          for (int i = 0; i < 4; i++) { const bool up = lane & 2; const float snd = up ? a[i] : a[i + 4]; a[i] = (up ? a[i + 4] : a[i]) + __shfl_xor_sync(~0u, snd, 2); }
          #pragma unroll
          for (int i = 0; i < 2; i++) { const bool up = lane & 4; const float snd = up ? a[i] : a[i + 2]; a[i] = (up ? a[i + 2] : a[i]) + __shfl_xor_sync(~0u, snd, 4); }
          { const bool up = lane & 8; const float snd = up ? a[0] : a[1]; a[0] = (up ? a[1] : a[0]) + __shfl_xor_sync(~0u, snd, 8); }
          a[0] += __shfl_xor_sync(~0u, a[0], 16);
          if (lane < 16) s_red[w * 16 + (lane & 1) * 8 + ((lane >> 1) & 1) * 4 + ((lane >> 2) & 1) * 2 + (lane >> 3)] = a[0];
          bar_sync(NB_HELP, 64);
          if (t64 < 16) st_tagged(dst + t64, s_red[t64] + s_red[16 + t64], tag);
          bar_sync(NB_HELP, 64);
        };
        if (bid < 120) slab_sum(bar + B_SLAB, g_colsum + bid * 16);
        mbar_arrive(bar + B_SLABFREE);
        {
          const float2* pc = g_colsum + cbA * 240 + t64;
          const int i3 = t64 < 48 ? 192 : 0;
          float c0, c1, c2, c3; bool ok; int spins = 0;
          do { ok = ld_tagged(pc, c0, tag); ok &= ld_tagged(pc + 64, c1, tag); ok &= ld_tagged(pc + 128, c2, tag); ok &= ld_tagged(pc + i3, c3, tag); } while (!ok && ++spins < (1 << 20));
          s_cs[t64] = c0; s_cs[64 + t64] = c1; s_cs[128 + t64] = c2; if (t64 < 48) s_cs[192 + t64] = c3;
        }
        {
          const float2* pr = g_rowstat + 2 * (rbA * 128 + t64);
          float m0, v0, m1, v1; bool ok; int spins = 0;
          do { ok = ld_tagged(pr, m0, tag); ok &= ld_tagged(pr + 1, v0, tag); ok &= ld_tagged(pr + 128, m1, tag); ok &= ld_tagged(pr + 129, v1, tag); } while (!ok && ++spins < (1 << 20));
          const float ra = 1.f / sqrtf(v0 + LN_EPS), rc = 1.f / sqrtf(v1 + LN_EPS);
          s_row[t64] = make_float4(m0, ra, ra / sqrtf(v0 * ra * ra + LN_EPS), 0.f);
          s_row[64 + t64] = make_float4(m1, rc, rc / sqrtf(v1 * rc * rc + LN_EPS), 0.f);
        }
        mbar_arrive(bar + B_PREADY);
        if (t64 == 0) TRACE(0, 8);
        if (bid < 96) slab_sum(bar + B_SLAB + 8, g_colsum + NQKV + bid * 16);
        {
          const float e0 = __bfloat162float(b1[cbA * 192 + t64]), e1 = __bfloat162float(b1[cbA * 192 + 64 + t64]), e2 = __bfloat162float(b1[cbA * 192 + 128 + t64]);
          const float2* pc = g_colsum + NQKV + cbA * 192 + t64;
          float c0, c1, c2; bool ok; int spins = 0;
          do { ok = ld_tagged(pc, c0, tag); ok &= ld_tagged(pc + 64, c1, tag); ok &= ld_tagged(pc + 128, c2, tag); } while (!ok && ++spins < (1 << 20));
          s_cs1[t64] = c0; s_cs1[64 + t64] = c1; s_cs1[128 + t64] = c2;
          s_b1h[t64] = 0.5f * e0; s_b1h[64 + t64] = 0.5f * e1; s_b1h[128 + t64] = 0.5f * e2;
        }
        mbar_arrive(bar + B_PREADY + 8);
        if (t64 == 0) TRACE(0, 10);
      }
    }
    cluster_sync();
    return;
  }

  asm volatile("setmaxnreg.inc.sync.aligned.u32 112;");
  const int w4 = warp & 3, g = lane >> 2, t = lane & 3;
  const int mi = wg & 1, ni = wg >> 1;
  {
    const float tag = __uint_as_float(__ldcg(&g_epoch) + 1u);
    const int row = bid * 16 + warp;
    const uint2* px = reinterpret_cast<const uint2*>(x + (size_t)row * DM);
    float v[20], sum = 0.f, sq = 0.f;
    #pragma unroll
    for (int i = 0; i < 5; i++) {
      const uint2 u = __ldg(px + i * 32 + lane);
      v[4 * i] = bf_lo(u.x); v[4 * i + 1] = bf_hi(u.x); v[4 * i + 2] = bf_lo(u.y); v[4 * i + 3] = bf_hi(u.y);
      sum += (v[4 * i] + v[4 * i + 1]) + (v[4 * i + 2] + v[4 * i + 3]);
    }
    #pragma unroll
    for (int o = 16; o; o >>= 1) sum += __shfl_xor_sync(~0u, sum, o);
    const float mean = sum * (1.f / DM);
    #pragma unroll
    for (int i = 0; i < 20; i++) { const float d = v[i] - mean; sq = fmaf(d, d, sq); }
    #pragma unroll
    for (int o = 16; o; o >>= 1) sq += __shfl_xor_sync(~0u, sq, o);
    if (lane < 2) st_tagged(g_rowstat + 2 * row + lane, lane ? sq * (1.f / DM) : mean, tag);
  }
  int s = 0; uint32_t ph = 0;
  const int tg0 = rbA * 16 + mi * 8 + w4 * 2;
  {
    float acc[60];
    #pragma unroll 1
    for (int kb = 0; kb < 10; kb++) {
      if (kb == LAG_A && ni == 1) bar_sync(NB_LAG, 512);
      mbar_wait(bar + B_FULL + 8 * s, ph);
      if (tid == 0 && kb == 0) TRACE(0, 1);
      const uint32_t alo = ((sd + s * AB_STAGE + mi * 8192) >> 4) | (1u << 16);
      const uint32_t blo = ((sd + s * AB_STAGE + 16384 + ni * 8192) >> 4) | (256u << 16);
      wg_fence();
      #pragma unroll
      for (int k = 0; k < 4; k++) wgmma_n120_ss(acc, alo + k * 2, 64u | (1u << 30), blo + (k >> 1) * 1024 + (k & 1) * 128, 64u | (1u << 30), (kb | k) != 0);
      wg_commit();
      if (LAG_A < 10 && kb == 9 && ni == 0) asm volatile("bar.arrive %0, 512;" ::"n"(NB_LAG) : "memory");
      if (kb > 0) { wg_wait<1>(); if (lane < 2) mbar_arrive_cta(bar + B_EMPTY + 8 * ((s + 3) & 3), lane); }
      if (++s == 4) { s = 0; ph ^= 1; }
    }
    wg_wait<0>();
    if (lane < 2) mbar_arrive_cta(bar + B_EMPTY + 8 * ((s + 3) & 3), lane);
    if (tid == 0) TRACE(0, 2); if (tid == 384) TRACE(1, 8);
    mbar_wait(bar + B_PREADY, 0);
    const float4 st0 = s_row[mi * 64 + w4 * 16 + g], st1 = s_row[mi * 64 + w4 * 16 + g + 8];
    const float nm0 = -st0.x, nm1 = -st1.x;
    uint32_t* dbase = reinterpret_cast<uint32_t*>(g_qkv + ((size_t)(cbA * 12 + ni * 6) * 256 + tg0) * 192) + lane;
    const uint32_t kaug0 = ((MUFU_MASK >> (tg0 & 15)) & 1) ? 0u : 0x3B8043C0u;
    const uint32_t kaug1 = ((MUFU_MASK >> ((tg0 + 1) & 15)) & 1) ? 0u : 0x3B8043C0u;
    #pragma unroll
    for (int pi = 0; pi < 3; pi++) {
      const int P = cbA * 6 + ni * 3 + pi, sec = P >> 4;
      const float sc = sec == 0 ? QSCALE : 1.f;
      const float r0 = st0.y * sc, r1 = st1.y * sc;
      uint32_t* de = dbase + pi * 2 * 256 * 96;
      uint32_t* dod = de + 256 * 96;
      uint32_t w[5][2];
      #pragma unroll
      for (int gi = 0; gi < 5; gi++) {
        const int i = pi * 5 + gi;
        const float2 cs = *reinterpret_cast<const float2*>(s_cs + ni * 120 + 8 * i + 2 * t);
        w[gi][0] = pack_bf16(fmaf(nm0, cs.x, acc[4 * i]) * r0, fmaf(nm0, cs.y, acc[4 * i + 1]) * r0);
        w[gi][1] = pack_bf16(fmaf(nm1, cs.x, acc[4 * i + 2]) * r1, fmaf(nm1, cs.y, acc[4 * i + 3]) * r1);
      }
      const uint32_t aug0 = sec == 1 ? kaug0 : (sec == 0 ? 0x3F803F80u : 0x00003F80u);
      const uint32_t aug1 = sec == 1 ? kaug1 : (sec == 0 ? 0x3F803F80u : 0x00003F80u);
      const uint32_t ae0 = t == 2 ? aug0 : 0u, ae1 = t == 2 ? aug1 : 0u, ao0 = t == 0 ? aug0 : 0u, ao1 = t == 0 ? aug1 : 0u;
      de[0] = w[0][0];  de[96] = w[0][1];  de[32] = w[1][0];  de[96 + 32] = w[1][1];
      de[64] = t < 2 ? w[2][0] : ae0;   de[96 + 64] = t < 2 ? w[2][1] : ae1;
      dod[0] = w[3][0]; dod[96] = w[3][1]; dod[32] = w[4][0]; dod[96 + 32] = w[4][1];
      dod[64] = t >= 2 ? w[2][0] : ao0; dod[96 + 64] = t >= 2 ? w[2][1] : ao1;
      if (sec == 1) {
        uint32_t e0 = hfma2_bf16(w[1][0], w[1][0], hmul2_bf16(w[0][0], w[0][0])), e1 = hfma2_bf16(w[1][1], w[1][1], hmul2_bf16(w[0][1], w[0][1]));
        uint32_t o0 = hfma2_bf16(w[4][0], w[4][0], hmul2_bf16(w[3][0], w[3][0])), o1 = hfma2_bf16(w[4][1], w[4][1], hmul2_bf16(w[3][1], w[3][1]));
        if (t < 2) { e0 = hfma2_bf16(w[2][0], w[2][0], e0); e1 = hfma2_bf16(w[2][1], w[2][1], e1); }
        else       { o0 = hfma2_bf16(w[2][0], w[2][0], o0); o1 = hfma2_bf16(w[2][1], w[2][1], o1); }
        float fe0 = bf_lo(e0) + bf_hi(e0), fe1 = bf_lo(e1) + bf_hi(e1), fo0 = bf_lo(o0) + bf_hi(o0), fo1 = bf_lo(o1) + bf_hi(o1);
        #pragma unroll
        for (int o = 1; o < 4; o <<= 1) {
          fe0 += __shfl_xor_sync(~0u, fe0, o); fe1 += __shfl_xor_sync(~0u, fe1, o); fo0 += __shfl_xor_sync(~0u, fo0, o); fo1 += __shfl_xor_sync(~0u, fo1, o);
        }
        const unsigned me = __reduce_max_sync(~0u, max(__float_as_uint(fe0) & 0x7FFFFFFFu, __float_as_uint(fe1) & 0x7FFFFFFFu));
        const unsigned mo = __reduce_max_sync(~0u, max(__float_as_uint(fo0) & 0x7FFFFFFFu, __float_as_uint(fo1) & 0x7FFFFFFFu));
        if (lane == 0) { float* kn = g_knorm + (size_t)(2 * P - 32) * 128 + (tg0 >> 1); kn[0] = __uint_as_float(me); kn[128] = __uint_as_float(mo); }
      } else if (sec == 2) {
        unsigned m = 0;
        #pragma unroll
        for (int gi = 0; gi < 5; gi++) m = __vmaxu2(m, __vmaxu2(w[gi][0] & 0x7FFF7FFFu, w[gi][1] & 0x7FFF7FFFu));
        m = __reduce_max_sync(~0u, max(m << 16, m & 0xFFFF0000u));
        if (lane == 0) { float* vm = g_vmax + (size_t)(2 * P - 64) * 128 + (tg0 >> 1); vm[0] = __uint_as_float(m); vm[128] = __uint_as_float(m); }
      }
    }
    asm volatile("bar.arrive %0, 544;" ::"n"(NB_QKV) : "memory");
  }
  if (tid == 0) TRACE(0, 4); if (tid == 384) TRACE(1, 9);
  uint32_t qa[8];
  unsigned kmax_bits, vmax_bits;
  auto load_q = [&](int tg) {
    const uint32_t* qp = reinterpret_cast<const uint32_t*>(g_qkv + ((size_t)hd * 256 + tg) * 192) + lane;
    qa[0] = __ldcg(qp); qa[1] = __ldcg(qp + 96); qa[2] = __ldcg(qp + 32); qa[3] = __ldcg(qp + 96 + 32);
    qa[4] = __ldcg(qp + 64); qa[5] = __ldcg(qp + 96 + 64); qa[6] = 0; qa[7] = 0;
    asm volatile("" : "+r"(qa[6]), "+r"(qa[7]));
  };
  {
    float acc[48];
    #pragma unroll 1
    for (int kb = 0; kb < 10; kb++) {
      mbar_wait(bar + B_FULL + 8 * s, ph);
      const uint32_t alo = ((sd + s * AB_STAGE + mi * 8192) >> 4) | (1u << 16);
      const uint32_t blo = ((sd + s * AB_STAGE + 16384 + ni * 3 * 2048) >> 4) | (128u << 16);
      wg_fence();
      #pragma unroll
      for (int k = 0; k < 4; k++) wgmma_n96_ss(acc, alo + k * 2, 64u | (1u << 30), blo + (k >> 1) * 768 + (k & 1) * 64, 32u | (2u << 30), (kb | k) != 0);
      wg_commit();
      if (kb > 0) { wg_wait<1>(); if (lane < 2) mbar_arrive_cta(bar + B_EMPTY + 8 * ((s + 3) & 3), lane); }
      if (++s == 4) { s = 0; ph ^= 1; }
    }
    wg_wait<0>();
    if (lane < 2) mbar_arrive_cta(bar + B_EMPTY + 8 * ((s + 3) & 3), lane);
    if (tid == 0) TRACE(0, 5); if (tid == 384) TRACE(1, 10);
    mbar_wait(bar + B_QKV, 0);
    load_q(qq * 64 + wg * 16 + w4 * 2);
    const float4 kn4 = __ldcg(reinterpret_cast<const float4*>(g_knorm + hd * 128) + lane), vm4 = __ldcg(reinterpret_cast<const float4*>(g_vmax + hd * 128) + lane);
    kmax_bits = max(max(__float_as_uint(kn4.x), __float_as_uint(kn4.y)), max(__float_as_uint(kn4.z), __float_as_uint(kn4.w)));
    vmax_bits = max(max(__float_as_uint(vm4.x), __float_as_uint(vm4.y)), max(__float_as_uint(vm4.z), __float_as_uint(vm4.w)));
    mbar_wait(bar + B_PREADY + 8, 0);
    const float4 st0 = s_row[mi * 64 + w4 * 16 + g], st1 = s_row[mi * 64 + w4 * 16 + g + 8];
    const float nm0 = -st0.x, nm1 = -st1.x, a0 = 0.5f * st0.z, a1 = 0.5f * st1.z;
    uint32_t* dst = reinterpret_cast<uint32_t*>(g_hid + ((size_t)(rbA * 24 + cbA * 3) * 16 + mi * 8 + w4 * 2) * 512) + lane;
    constexpr float GA = 1.5957691216057308f, GB = 1.5957691216057308f * 0.044715f * 4.f;
    #pragma unroll
    for (int i = 0; i < 12; i++) {
      const float2 cs = *reinterpret_cast<const float2*>(s_cs1 + ni * 96 + 8 * i + 2 * t);
      const float2 bb = *reinterpret_cast<const float2*>(s_b1h + ni * 96 + 8 * i + 2 * t);
      float h[4];
      h[0] = fmaf(fmaf(nm0, cs.x, acc[4 * i]), a0, bb.x);     h[1] = fmaf(fmaf(nm0, cs.y, acc[4 * i + 1]), a0, bb.y);
      h[2] = fmaf(fmaf(nm1, cs.x, acc[4 * i + 2]), a1, bb.x); h[3] = fmaf(fmaf(nm1, cs.y, acc[4 * i + 3]), a1, bb.y);
      #pragma unroll
      for (int e = 0; e < 4; e++) {
        const float u = h[e] * fmaf(h[e] * h[e], GB, GA);
        h[e] = fmaf(h[e], tanh_fast(u), h[e]);
      }
      const int kgl = ni * 12 + i;
      uint32_t* d = dst + (kgl >> 3) * 4096 + (kgl & 7) * 32;
      d[0] = pack_bf16(h[0], h[1]);
      d[256] = pack_bf16(h[2], h[3]);
    }
    asm volatile("bar.arrive %0, 544;" ::"n"(NB_HID) : "memory");
  }
  if (tid == 0) TRACE(0, 6); if (tid == 384) TRACE(1, 11);
  {
    const float kmax2 = __uint_as_float(__reduce_max_sync(~0u, kmax_bits)), vmax = __uint_as_float(__reduce_max_sync(~0u, vmax_bits));
    const bool odd = hd & 1;
    const uint32_t kv0 = sd >> 4, bb = bar + B_KV;
    constexpr uint32_t TB = KV_TILE >> 4, VOFF = (6144 >> 4) + (24u << 16);
    constexpr uint32_t FREE_MASK = (1u << 2) | (1u << 4) | (1u << 6) | (1u << 9) | (1u << 11) | (1u << 13);
    uint32_t one2 = 0x3F803F80u;
    asm volatile("" : "+r"(one2));

    #pragma unroll 1
    for (int r = 0; r < 2; r++) {
      const int tg = qq * 64 + wg * 16 + r * 8 + w4 * 2;
      if (r == 1) load_q(tg);
      const bool real2 = odd ? (t >= 2) : (t < 2);
      float n0 = bf_lo(qa[0]) * bf_lo(qa[0]) + bf_hi(qa[0]) * bf_hi(qa[0]) + bf_lo(qa[2]) * bf_lo(qa[2]) + bf_hi(qa[2]) * bf_hi(qa[2]);
      float n1 = bf_lo(qa[1]) * bf_lo(qa[1]) + bf_hi(qa[1]) * bf_hi(qa[1]) + bf_lo(qa[3]) * bf_lo(qa[3]) + bf_hi(qa[3]) * bf_hi(qa[3]);
      if (real2) { n0 += bf_lo(qa[4]) * bf_lo(qa[4]) + bf_hi(qa[4]) * bf_hi(qa[4]); n1 += bf_lo(qa[5]) * bf_lo(qa[5]) + bf_hi(qa[5]) * bf_hi(qa[5]); }
      n0 += __shfl_xor_sync(~0u, n0, 1); n0 += __shfl_xor_sync(~0u, n0, 2);
      n1 += __shfl_xor_sync(~0u, n1, 1); n1 += __shfl_xor_sync(~0u, n1, 2);
      const bool ok = (n0 * kmax2 * 1.06f <= FAST_BOUND2) && (n1 * kmax2 * 1.06f <= FAST_BOUND2) && (vmax <= FAST_VMAX);
      int allok;
      asm volatile("{\n.reg .pred p, q;\nsetp.ne.b32 p, %1, 0;\nbarrier.red.and.pred q, %2, 128, p;\nselp.b32 %0, 1, 0, q;\n}" : "=r"(allok) : "r"((int)ok), "r"(NB_WG + wg) : "memory");
      allok = __shfl_sync(~0u, allok, 0);
      float o[12];
      #pragma unroll
      for (int i = 0; i < 12; i++) o[i] = 0.f;
      int freed = 0;
      if (allok) {
        float s0[32], s1[32]; uint32_t p[16];
        if (r == 0) mbar_wait(bb, 0);
        if (tid == 0) TRACE(1, 2 + r); if (tid == 384) TRACE(1, 12 + r);
        wg_fence(); issue_qk(s0, qa, kv0); wg_commit(); wg_wait<0>();
        #pragma unroll 1
        for (int j = 0; j < 16; j++) {
          const uint32_t base = kv0 + j * TB;
          wg_fence(); issue_qk(s1, qa, base + 192u); wg_commit();
          exp_tile(s0, p, MUFU_MASK & 0xFF, one2);
          wg_fence(); issue_pv(o, p, base + VOFF); wg_commit();
          if (r == 0 && j < 15) mbar_wait(bb + (j + 1) * 8, 0);
          wg_wait<0>();
          wg_fence(); issue_qk(s0, qa, j < 15 ? base + TB : base); wg_commit();
          exp_tile(s1, p, MUFU_MASK >> 8, one2);
          wg_fence(); issue_pv(o, p, base + VOFF + 4 * 48u); wg_commit();
          wg_wait<0>();
          if (r == 1 && ((FREE_MASK >> j) & 1)) { if (lane < 2) mbar_arrive_cta(bar + B_KVFREE + 8 * freed, lane); freed++; }
        }
      } else {
        if (!real2) { qa[4] = 0; qa[5] = 0; }
        float m0 = -INFINITY, m1 = -INFINITY;
        float sc[32]; uint32_t p[16];
        #pragma unroll 1
        for (int u = 0; u < 32; u++) {
          const uint32_t base = kv0 + (u >> 1) * TB;
          mbar_wait(bb + (u >> 1) * 8, 0);
          wg_fence(); issue_qk(sc, qa, base + (u & 1) * 192u); wg_commit(); wg_wait<0>();
          float x0 = m0, x1 = m1;
          #pragma unroll
          for (int i = 0; i < 8; i++) { x0 = fmaxf(x0, fmaxf(sc[4 * i], sc[4 * i + 1])); x1 = fmaxf(x1, fmaxf(sc[4 * i + 2], sc[4 * i + 3])); }
          x0 = fmaxf(x0, __shfl_xor_sync(~0u, x0, 1)); x0 = fmaxf(x0, __shfl_xor_sync(~0u, x0, 2));
          x1 = fmaxf(x1, __shfl_xor_sync(~0u, x1, 1)); x1 = fmaxf(x1, __shfl_xor_sync(~0u, x1, 2));
          const float c0 = ex2(m0 - x0), c1 = ex2(m1 - x1);
          m0 = x0; m1 = x1;
          #pragma unroll
          for (int i = 0; i < 3; i++) { o[4 * i] *= c0; o[4 * i + 1] *= c0; o[4 * i + 2] *= c1; o[4 * i + 3] *= c1; }
          #pragma unroll
          for (int i = 0; i < 8; i++) {
            p[2 * i] = pack_bf16(ex2(sc[4 * i] - m0), ex2(sc[4 * i + 1] - m0));
            p[2 * i + 1] = pack_bf16(ex2(sc[4 * i + 2] - m1), ex2(sc[4 * i + 3] - m1));
          }
          wg_fence(); issue_pv(o, p, base + VOFF + (u & 1) * 4 * 48u); wg_commit(); wg_wait<0>();
        }
        if (r == 1 && lane < 2) for (int i = 0; i < 6; i++) mbar_arrive_cta(bar + B_KVFREE + 8 * i, lane);
      }
      const int src = (lane & ~3) | (odd ? 0 : 2);
      const float i0 = 1.f / __shfl_sync(~0u, o[8], src), i1 = 1.f / __shfl_sync(~0u, o[10], src);
      const int kg0 = (20 * hd) >> 3;
      uint32_t* ob = reinterpret_cast<uint32_t*>(g_att + ((size_t)(tg >> 4) * 10 * 16 + (tg & 15)) * 512) + lane;
      auto kaddr = [&](int kg) { return ob + (kg >> 3) * 4096 + (kg & 7) * 32; };
      uint32_t* d0 = kaddr(odd ? kg0 + 1 : kg0);
      uint32_t* d1 = kaddr(odd ? kg0 + 2 : kg0 + 1);
      uint32_t* d2 = kaddr(odd ? kg0 : kg0 + 2);
      d0[0] = pack_bf16(o[0] * i0, o[1] * i0); d0[256] = pack_bf16(o[2] * i1, o[3] * i1);
      d1[0] = pack_bf16(o[4] * i0, o[5] * i0); d1[256] = pack_bf16(o[6] * i1, o[7] * i1);
      if (real2) { d2[0] = pack_bf16(o[8] * i0, o[9] * i0); d2[256] = pack_bf16(o[10] * i1, o[11] * i1); }
    }
    asm volatile("bar.arrive %0, 544;" ::"n"(NB_ATT) : "memory");
  }
  if (tid == 0) TRACE(1, 4); if (tid == 384) TRACE(1, 14);
  auto phase_d = [&](auto nseg_c, auto mma, auto& acc) {
    constexpr int NSEG = decltype(nseg_c)::value;
    constexpr int NIT = NSEG / 2;
    const int col0 = cbD * 160 + wg * 96, row0 = rbD * 64 + w4 * 16;
    uint4 xv[NIT];
    #pragma unroll
    for (int it = 0; it < NIT; it++) {
      const int idx = it * 32 + lane, r = idx / NSEG, c8 = idx % NSEG;
      xv[it] = __ldg(reinterpret_cast<const uint4*>(x + (size_t)(row0 + r) * DM + col0 + c8 * 8));
    }
    int sD = 0; uint32_t phD = 0;
    #pragma unroll 1
    for (int kb = 0; kb < 34; kb++) {
      mbar_wait(bar + B_DFULL + 8 * sD, phD);
      if (tid == 0 && kb == 0) TRACE(2, 1);
      if (tid == 0 && kb == 24) TRACE(2, 2);
      const uint32_t alo = ((sd + sD * D_STAGE) >> 4) | (8u << 16);
      const uint32_t blo = ((sd + sD * D_STAGE + 8192 + wg * 3 * 2048) >> 4) | (128u << 16);
      wg_fence();
      #pragma unroll
      for (int k = 0; k < 4; k++) mma(acc, alo + k * 16, blo + (k >> 1) * 640 + (k & 1) * 64, (kb | k) != 0);
      wg_commit();
      if (kb > 0) { wg_wait<1>(); if (lane < 2) mbar_arrive_cta(bar + B_DEMPTY + 8 * (sD == 0 ? 5 : sD - 1), lane); }
      if (++sD == 6) { sD = 0; phD ^= 1; }
    }
    wg_wait<0>();
    if (tid == 0) TRACE(2, 3);
    float* stg = reinterpret_cast<float*>(smem) + warp * (16 * 100);
    uint4 bv[NIT];
    #pragma unroll
    for (int it = 0; it < NIT; it++) bv[it] = __ldg(reinterpret_cast<const uint4*>(b2 + col0 + ((it * 32 + lane) % NSEG) * 8));
    bar_sync(NB_FIN, 256);
    #pragma unroll
    for (int i = 0; i < NSEG; i++) {
      *reinterpret_cast<float2*>(stg + g * 100 + 8 * i + 2 * t) = make_float2(acc[4 * i], acc[4 * i + 1]);
      *reinterpret_cast<float2*>(stg + (g + 8) * 100 + 8 * i + 2 * t) = make_float2(acc[4 * i + 2], acc[4 * i + 3]);
    }
    __syncwarp();
    #pragma unroll
    for (int it = 0; it < NIT; it++) {
      const int idx = it * 32 + lane, r = idx / NSEG, c8 = idx % NSEG;
      const float4 a0 = *reinterpret_cast<const float4*>(stg + r * 100 + c8 * 8), a1 = *reinterpret_cast<const float4*>(stg + r * 100 + c8 * 8 + 4);
      uint4 o;
      o.x = pack_bf16(a0.x + bf_lo(bv[it].x) + bf_lo(xv[it].x), a0.y + bf_hi(bv[it].x) + bf_hi(xv[it].x));
      o.y = pack_bf16(a0.z + bf_lo(bv[it].y) + bf_lo(xv[it].y), a0.w + bf_hi(bv[it].y) + bf_hi(xv[it].y));
      o.z = pack_bf16(a1.x + bf_lo(bv[it].z) + bf_lo(xv[it].z), a1.y + bf_hi(bv[it].z) + bf_hi(xv[it].z));
      o.w = pack_bf16(a1.z + bf_lo(bv[it].w) + bf_lo(xv[it].w), a1.w + bf_hi(bv[it].w) + bf_hi(xv[it].w));
      *reinterpret_cast<uint4*>(out + (size_t)(row0 + r) * DM + col0 + c8 * 8) = o;
    }
    if (tid == 0) TRACE(2, 4);
  };
  if (wg == 0) {
    float acc[48];
    phase_d(IntC<12>{}, [](float (&a)[48], uint32_t da, uint32_t db, int sc) { wgmma_n96_ss(a, da, 64u, db, 32u | (2u << 30), sc); }, acc);
  } else if (wg == 1) {
    float acc[32];
    phase_d(IntC<8>{}, [](float (&a)[32], uint32_t da, uint32_t db, int sc) { wgmma_n64_ss(a, da, 64u, db, 32u | (2u << 30), sc); }, acc);
  }
  cluster_sync();
}

typedef CUresult (*EncodeTiledFn)(CUtensorMap*, CUtensorMapDataType, cuuint32_t, void*, const cuuint64_t*, const cuuint64_t*, const cuuint32_t*,
                                  const cuuint32_t*, CUtensorMapInterleave, CUtensorMapSwizzle, CUtensorMapL2promotion, CUtensorMapFloatOOBfill);

CUtensorMap make_map(EncodeTiledFn fn, const void* base, int rank, const cuuint64_t* dims, const cuuint64_t* strides, const cuuint32_t* box, CUtensorMapSwizzle sw) {
  CUtensorMap m;
  const cuuint32_t es[4] = {1, 1, 1, 1};
  CUresult rc = fn(&m, CU_TENSOR_MAP_DATA_TYPE_BFLOAT16, rank, const_cast<void*>(base), dims, strides, box, es, CU_TENSOR_MAP_INTERLEAVE_NONE, sw,
                   L2PROMO, CU_TENSOR_MAP_FLOAT_OOB_FILL_NONE);
  (void)rc;
  return m;
}

}

extern "C" void kernel_launch(void* const* d_in, const int* in_sizes, int n_in, void* d_out, int out_size) {
  const __nv_bfloat16* x = static_cast<const __nv_bfloat16*>(d_in[0]);
  const __nv_bfloat16* wqkv = static_cast<const __nv_bfloat16*>(d_in[1]);
  const __nv_bfloat16* wo = static_cast<const __nv_bfloat16*>(d_in[2]);
  const __nv_bfloat16* w1 = static_cast<const __nv_bfloat16*>(d_in[4]);
  const __nv_bfloat16* b1 = static_cast<const __nv_bfloat16*>(d_in[5]);
  const __nv_bfloat16* w2 = static_cast<const __nv_bfloat16*>(d_in[6]);
  const __nv_bfloat16* b2 = static_cast<const __nv_bfloat16*>(d_in[7]);
  __nv_bfloat16* out = static_cast<__nv_bfloat16*>(d_out);

  static EncodeTiledFn encode = nullptr;
  if (!encode) {
    void* fn = nullptr;
    cudaDriverEntryPointQueryResult qr;
    cudaGetDriverEntryPoint("cuTensorMapEncodeTiled", &fn, cudaEnableDefault, &qr);
    encode = reinterpret_cast<EncodeTiledFn>(fn);
    cudaFuncSetAttribute(fused_block, cudaFuncAttributeMaxDynamicSharedMemorySize, SMEM_BYTES);
  }
  Maps tm;
  { const cuuint64_t d[2] = {DM, S_LEN}, st[1] = {DM * 2}; const cuuint32_t b[2] = {64, 128}; tm.x = make_map(encode, x, 2, d, st, b, CU_TENSOR_MAP_SWIZZLE_128B); }
  { const cuuint64_t d[2] = {NQKV, DM}, st[1] = {NQKV * 2}; const cuuint32_t b[2] = {64, 32}; tm.wqkv = make_map(encode, wqkv, 2, d, st, b, CU_TENSOR_MAP_SWIZZLE_128B); }
  { const cuuint64_t d[4] = {64, DM, 2, 16}, st[3] = {NQKV * 2, 128, 240}; const cuuint32_t b[4] = {64, 32, 2, 2}; tm.wq4 = make_map(encode, wqkv, 4, d, st, b, CU_TENSOR_MAP_SWIZZLE_128B); }
  { const cuuint64_t d[3] = {32, DM, FF / 32}, st[2] = {FF * 2, 64}; const cuuint32_t b[3] = {32, 32, 6}; tm.w1 = make_map(encode, w1, 3, d, st, b, CU_TENSOR_MAP_SWIZZLE_64B); }
  { const cuuint64_t d[2] = {NQKV, DM}, st[1] = {NQKV * 2}; const cuuint32_t b[2] = {16, 160}; tm.sq = make_map(encode, wqkv, 2, d, st, b, CU_TENSOR_MAP_SWIZZLE_NONE); }
  { const cuuint64_t d[2] = {FF, DM}, st[1] = {FF * 2}; const cuuint32_t b[2] = {16, 160}; tm.s1 = make_map(encode, w1, 2, d, st, b, CU_TENSOR_MAP_SWIZZLE_NONE); }
  { const cuuint64_t d[3] = {32, FF, DM / 32}, st[2] = {DM * 2, 64}; const cuuint32_t b[3] = {32, 32, 5}; tm.w2 = make_map(encode, w2, 3, d, st, b, CU_TENSOR_MAP_SWIZZLE_64B); }
  { const cuuint64_t d[3] = {32, DM, DM / 32}, st[2] = {DM * 2, 64}; const cuuint32_t b[3] = {32, 32, 5}; tm.wo = make_map(encode, wo, 3, d, st, b, CU_TENSOR_MAP_SWIZZLE_64B); }

  cudaLaunchAttribute at[1];
  at[0].id = cudaLaunchAttributeClusterDimension; at[0].val.clusterDim.x = 2; at[0].val.clusterDim.y = 1; at[0].val.clusterDim.z = 1;
  cudaLaunchConfig_t cfg = {};
  cfg.stream = cudaStreamPerThread;
  cfg.gridDim = dim3(128); cfg.blockDim = dim3(640); cfg.dynamicSmemBytes = SMEM_BYTES; cfg.attrs = at; cfg.numAttrs = 1;
  cudaLaunchKernelEx(&cfg, fused_block, tm, x, wqkv, w1, b1, w2, wo, b2, out);
}
```

```cpp
#include <cuda_runtime.h>
#include <cuda_bf16.h>
#include <cuda.h>
#include <stdint.h>

namespace {

constexpr int S_LEN = 2048, DM = 640, NH = 32, FF = 1536, NQKV = 1920;
constexpr float LN_EPS = 1e-5f;

__device__ __align__(1024) __nv_bfloat16 g_qkv[3 * NH * 256 * 192];
__device__ __align__(1024) __nv_bfloat16 g_hid[16 * 24 * 8192];
__device__ __align__(1024) __nv_bfloat16 g_att[16 * 10 * 8192];
__device__ float2 g_rowstat[2 * S_LEN];
__device__ float2 g_colsum[NQKV + FF];
__device__ float g_knorm[NH * 128];
__device__ float g_vmax[NH * 128];
__device__ unsigned g_epoch;
__device__ unsigned g_cnt[6 * 32];

#define TRACE(k, i)

__device__ __forceinline__ uint32_t smem_u32(const void* p) { return (uint32_t)__cvta_generic_to_shared(p); }
__device__ __forceinline__ void wg_fence() { asm volatile("wgmma.fence.sync.aligned;" ::: "memory"); }
__device__ __forceinline__ void wg_commit() { asm volatile("wgmma.commit_group.sync.aligned;" ::: "memory"); }
template <int N> __device__ __forceinline__ void wg_wait() { asm volatile("wgmma.wait_group.sync.aligned %0;" ::"n"(N) : "memory"); }
__device__ __forceinline__ void mbar_init(uint32_t bar, int cnt) { asm volatile("mbarrier.init.shared::cta.b64 [%0], %1;" ::"r"(bar), "r"(cnt)); }
__device__ __forceinline__ void mbar_expect(uint32_t bar, uint32_t bytes) {
  asm volatile("mbarrier.arrive.expect_tx.shared::cta.b64 _, [%0], %1;" ::"r"(bar), "r"(bytes) : "memory");
}
__device__ __forceinline__ void mbar_expect_only(uint32_t bar, uint32_t bytes) {
  asm volatile("mbarrier.expect_tx.relaxed.cta.shared::cta.b64 [%0], %1;" ::"r"(bar), "r"(bytes) : "memory");
}
__device__ __forceinline__ void mbar_arrive(uint32_t bar) { asm volatile("mbarrier.arrive.shared::cta.b64 _, [%0];" ::"r"(bar) : "memory"); }
__device__ __forceinline__ void mbar_arrive_cta(uint32_t bar, uint32_t cta) {
  asm volatile("{\n.reg .b32 r;\nmapa.shared::cluster.u32 r, %0, %1;\nmbarrier.arrive.shared::cluster.b64 _, [r];\n}" ::"r"(bar), "r"(cta) : "memory");
}
__device__ __forceinline__ void mbar_wait(uint32_t bar, uint32_t parity) {
  asm volatile("{\n.reg .pred p;\nWAIT:\nmbarrier.try_wait.parity.shared::cta.b64 p, [%0], %1;\n@p bra DONE;\nbra WAIT;\nDONE:\n}" ::"r"(bar), "r"(parity) : "memory");
}
__device__ __forceinline__ void bulk_load(uint32_t dst, const void* src, uint32_t bytes, uint32_t bar) {
  asm volatile("cp.async.bulk.shared::cluster.global.mbarrier::complete_tx::bytes [%0], [%1], %2, [%3];" ::"r"(dst), "l"(src), "r"(bytes), "r"(bar) : "memory");
}
__device__ __forceinline__ void tma_2d(uint32_t dst, const CUtensorMap* tm, int c0, int c1, uint32_t bar) {
  asm volatile("cp.async.bulk.tensor.2d.shared::cluster.global.mbarrier::complete_tx::bytes [%0], [%1, {%3, %4}], [%2];" ::"r"(dst), "l"(tm), "r"(bar), "r"(c0), "r"(c1) : "memory");
}
__device__ __forceinline__ void tma_2d_mc(uint32_t dst, const CUtensorMap* tm, int c0, int c1, uint32_t bar, uint16_t mask) {
  asm volatile("cp.async.bulk.tensor.2d.shared::cluster.global.mbarrier::complete_tx::bytes.multicast::cluster [%0], [%1, {%3, %4}], [%2], %5;" ::"r"(dst), "l"(tm), "r"(bar), "r"(c0), "r"(c1), "h"(mask) : "memory");
}
__device__ __forceinline__ void tma_3d_mc(uint32_t dst, const CUtensorMap* tm, int c0, int c1, int c2, uint32_t bar, uint16_t mask) {
  asm volatile("cp.async.bulk.tensor.3d.shared::cluster.global.mbarrier::complete_tx::bytes.multicast::cluster [%0], [%1, {%3, %4, %5}], [%2], %6;" ::"r"(dst), "l"(tm), "r"(bar), "r"(c0), "r"(c1), "r"(c2), "h"(mask) : "memory");
}
__device__ __forceinline__ void tma_4d_mc(uint32_t dst, const CUtensorMap* tm, int c0, int c1, int c2, int c3, uint32_t bar, uint16_t mask) {
  asm volatile("cp.async.bulk.tensor.4d.shared::cluster.global.mbarrier::complete_tx::bytes.multicast::cluster [%0], [%1, {%3, %4, %5, %6}], [%2], %7;" ::"r"(dst), "l"(tm), "r"(bar), "r"(c0), "r"(c1), "r"(c2), "r"(c3), "h"(mask) : "memory");
}
__device__ __forceinline__ void cluster_sync() { asm volatile("barrier.cluster.arrive.relaxed.aligned;\nbarrier.cluster.wait.aligned;" ::: "memory"); }
__device__ __forceinline__ void bar_sync(int id, int n) { asm volatile("bar.sync %0, %1;" ::"r"(id), "r"(n) : "memory"); }
__device__ __forceinline__ float ex2(float x) { float y; asm("ex2.approx.ftz.f32 %0, %1;" : "=f"(y) : "f"(x)); return y; }
__device__ __forceinline__ float tanh_fast(float x) { float y; asm("tanh.approx.f32 %0, %1;" : "=f"(y) : "f"(x)); return y; }
__device__ __forceinline__ uint32_t pack_bf16(float lo, float hi) { uint32_t r; asm("cvt.rn.bf16x2.f32 %0, %1, %2;" : "=r"(r) : "f"(hi), "f"(lo)); return r; }
__device__ __forceinline__ uint32_t hfma2_bf16(uint32_t a, uint32_t b, uint32_t c) { uint32_t r; asm("fma.rn.bf16x2 %0, %1, %2, %3;" : "=r"(r) : "r"(a), "r"(b), "r"(c)); return r; }
__device__ __forceinline__ uint32_t hmul2_bf16(uint32_t a, uint32_t b) { uint32_t r; asm("mul.rn.bf16x2 %0, %1, %2;" : "=r"(r) : "r"(a), "r"(b)); return r; }
template <int LUT> __device__ __forceinline__ uint32_t lop3(uint32_t a, uint32_t b, uint32_t c) {
  uint32_t r; asm("lop3.b32 %0, %1, %2, %3, %4;" : "=r"(r) : "r"(a), "r"(b), "r"(c), "n"(LUT)); return r;
}
__device__ __forceinline__ float bf_lo(uint32_t v) { return __uint_as_float(v << 16); }
__device__ __forceinline__ float bf_hi(uint32_t v) { return __uint_as_float(v & 0xFFFF0000u); }

__device__ __forceinline__ void wgmma_n120_ss(float (&d)[60], uint32_t alo, uint32_t ahi, uint32_t blo, uint32_t bhi, int scaleD) {
  asm volatile("{\n.reg .pred p;\n.reg .b64 da, db;\nsetp.ne.b32 p, %64, 0;\nmov.b64 da, {%60, %61};\nmov.b64 db, {%62, %63};\n"
    "wgmma.mma_async.sync.aligned.m64n120k16.f32.bf16.bf16 "
    "{%0,%1,%2,%3,%4,%5,%6,%7,%8,%9,%10,%11,%12,%13,%14,%15,%16,%17,%18,%19,%20,%21,%22,%23,%24,%25,%26,%27,%28,%29,%30,%31,%32,%33,%34,%35,%36,%37,%38,%39,%40,%41,%42,%43,%44,%45,%46,%47,%48,%49,%50,%51,%52,%53,%54,%55,%56,%57,%58,%59}, "
    "da, db, p, 1, 1, 0, 1;\n}\n"
    :
      "+f"(d[0]), "+f"(d[1]), "+f"(d[2]), "+f"(d[3]), "+f"(d[4]), "+f"(d[5]), "+f"(d[6]), "+f"(d[7]),
      "+f"(d[8]), "+f"(d[9]), "+f"(d[10]), "+f"(d[11]), "+f"(d[12]), "+f"(d[13]), "+f"(d[14]), "+f"(d[15]),
      "+f"(d[16]), "+f"(d[17]), "+f"(d[18]), "+f"(d[19]), "+f"(d[20]), "+f"(d[21]), "+f"(d[22]), "+f"(d[23]),
      "+f"(d[24]), "+f"(d[25]), "+f"(d[26]), "+f"(d[27]), "+f"(d[28]), "+f"(d[29]), "+f"(d[30]), "+f"(d[31]),
      "+f"(d[32]), "+f"(d[33]), "+f"(d[34]), "+f"(d[35]), "+f"(d[36]), "+f"(d[37]), "+f"(d[38]), "+f"(d[39]),
      "+f"(d[40]), "+f"(d[41]), "+f"(d[42]), "+f"(d[43]), "+f"(d[44]), "+f"(d[45]), "+f"(d[46]), "+f"(d[47]),
      "+f"(d[48]), "+f"(d[49]), "+f"(d[50]), "+f"(d[51]), "+f"(d[52]), "+f"(d[53]), "+f"(d[54]), "+f"(d[55]),
      "+f"(d[56]), "+f"(d[57]), "+f"(d[58]), "+f"(d[59])
    : "r"(alo), "r"(ahi), "r"(blo), "r"(bhi), "r"(scaleD));
}
__device__ __forceinline__ void wgmma_n96_ss(float (&d)[48], uint32_t alo, uint32_t ahi, uint32_t blo, uint32_t bhi, int scaleD) {
  asm volatile("{\n.reg .pred p;\n.reg .b64 da, db;\nsetp.ne.b32 p, %52, 0;\nmov.b64 da, {%48, %49};\nmov.b64 db, {%50, %51};\n"
    "wgmma.mma_async.sync.aligned.m64n96k16.f32.bf16.bf16 "
    "{%0,%1,%2,%3,%4,%5,%6,%7,%8,%9,%10,%11,%12,%13,%14,%15,%16,%17,%18,%19,%20,%21,%22,%23,%24,%25,%26,%27,%28,%29,%30,%31,%32,%33,%34,%35,%36,%37,%38,%39,%40,%41,%42,%43,%44,%45,%46,%47}, "
    "da, db, p, 1, 1, 0, 1;\n}\n"
    :
      "+f"(d[0]), "+f"(d[1]), "+f"(d[2]), "+f"(d[3]), "+f"(d[4]), "+f"(d[5]), "+f"(d[6]), "+f"(d[7]),
      "+f"(d[8]), "+f"(d[9]), "+f"(d[10]), "+f"(d[11]), "+f"(d[12]), "+f"(d[13]), "+f"(d[14]), "+f"(d[15]),
      "+f"(d[16]), "+f"(d[17]), "+f"(d[18]), "+f"(d[19]), "+f"(d[20]), "+f"(d[21]), "+f"(d[22]), "+f"(d[23]),
      "+f"(d[24]), "+f"(d[25]), "+f"(d[26]), "+f"(d[27]), "+f"(d[28]), "+f"(d[29]), "+f"(d[30]), "+f"(d[31]),
      "+f"(d[32]), "+f"(d[33]), "+f"(d[34]), "+f"(d[35]), "+f"(d[36]), "+f"(d[37]), "+f"(d[38]), "+f"(d[39]),
      "+f"(d[40]), "+f"(d[41]), "+f"(d[42]), "+f"(d[43]), "+f"(d[44]), "+f"(d[45]), "+f"(d[46]), "+f"(d[47])
    : "r"(alo), "r"(ahi), "r"(blo), "r"(bhi), "r"(scaleD));
}
__device__ __forceinline__ void wgmma_n64_ss(float (&d)[32], uint32_t alo, uint32_t ahi, uint32_t blo, uint32_t bhi, int scaleD) {
  asm volatile("{\n.reg .pred p;\n.reg .b64 da, db;\nsetp.ne.b32 p, %36, 0;\nmov.b64 da, {%32, %33};\nmov.b64 db, {%34, %35};\n"
    "wgmma.mma_async.sync.aligned.m64n64k16.f32.bf16.bf16 "
    "{%0,%1,%2,%3,%4,%5,%6,%7,%8,%9,%10,%11,%12,%13,%14,%15,%16,%17,%18,%19,%20,%21,%22,%23,%24,%25,%26,%27,%28,%29,%30,%31}, "
    "da, db, p, 1, 1, 0, 1;\n}\n"
    :
      "+f"(d[0]), "+f"(d[1]), "+f"(d[2]), "+f"(d[3]), "+f"(d[4]), "+f"(d[5]), "+f"(d[6]), "+f"(d[7]),
      "+f"(d[8]), "+f"(d[9]), "+f"(d[10]), "+f"(d[11]), "+f"(d[12]), "+f"(d[13]), "+f"(d[14]), "+f"(d[15]),
      "+f"(d[16]), "+f"(d[17]), "+f"(d[18]), "+f"(d[19]), "+f"(d[20]), "+f"(d[21]), "+f"(d[22]), "+f"(d[23]),
      "+f"(d[24]), "+f"(d[25]), "+f"(d[26]), "+f"(d[27]), "+f"(d[28]), "+f"(d[29]), "+f"(d[30]), "+f"(d[31])
    : "r"(alo), "r"(ahi), "r"(blo), "r"(bhi), "r"(scaleD));
}
__device__ __forceinline__ void wgmma_n64_rs(float (&d)[32], uint32_t a0, uint32_t a1, uint32_t a2, uint32_t a3, uint32_t blo, uint32_t bhi, int scaleD) {
  asm volatile("{\n.reg .pred p;\n.reg .b64 db;\nsetp.ne.b32 p, %38, 0;\nmov.b64 db, {%36, %37};\n"
    "wgmma.mma_async.sync.aligned.m64n64k16.f32.bf16.bf16 "
    "{%0,%1,%2,%3,%4,%5,%6,%7,%8,%9,%10,%11,%12,%13,%14,%15,%16,%17,%18,%19,%20,%21,%22,%23,%24,%25,%26,%27,%28,%29,%30,%31}, "
    "{%32, %33, %34, %35}, db, p, 1, 1, 0;\n}\n"
    :
      "+f"(d[0]), "+f"(d[1]), "+f"(d[2]), "+f"(d[3]), "+f"(d[4]), "+f"(d[5]), "+f"(d[6]), "+f"(d[7]),
      "+f"(d[8]), "+f"(d[9]), "+f"(d[10]), "+f"(d[11]), "+f"(d[12]), "+f"(d[13]), "+f"(d[14]), "+f"(d[15]),
      "+f"(d[16]), "+f"(d[17]), "+f"(d[18]), "+f"(d[19]), "+f"(d[20]), "+f"(d[21]), "+f"(d[22]), "+f"(d[23]),
      "+f"(d[24]), "+f"(d[25]), "+f"(d[26]), "+f"(d[27]), "+f"(d[28]), "+f"(d[29]), "+f"(d[30]), "+f"(d[31])
    : "r"(a0), "r"(a1), "r"(a2), "r"(a3), "r"(blo), "r"(bhi), "r"(scaleD));
}
__device__ __forceinline__ void wgmma_n24_rs(float (&d)[12], uint32_t a0, uint32_t a1, uint32_t a2, uint32_t a3, uint32_t blo, uint32_t bhi, int scaleD) {
  asm volatile("{\n.reg .pred p;\n.reg .b64 db;\nsetp.ne.b32 p, %18, 0;\nmov.b64 db, {%16, %17};\n"
    "wgmma.mma_async.sync.aligned.m64n24k16.f32.bf16.bf16 "
    "{%0,%1,%2,%3,%4,%5,%6,%7,%8,%9,%10,%11}, "
    "{%12, %13, %14, %15}, db, p, 1, 1, 1;\n}\n"
    :
      "+f"(d[0]), "+f"(d[1]), "+f"(d[2]), "+f"(d[3]), "+f"(d[4]), "+f"(d[5]), "+f"(d[6]), "+f"(d[7]),
      "+f"(d[8]), "+f"(d[9]), "+f"(d[10]), "+f"(d[11])
    : "r"(a0), "r"(a1), "r"(a2), "r"(a3), "r"(blo), "r"(bhi), "r"(scaleD));
}

#define MUFU_MASK_V 0x4949
constexpr uint32_t MUFU_MASK = MUFU_MASK_V;
constexpr float QSCALE = 0.22360679774997896f * 1.4426950408889634f;
constexpr float FAST_BOUND2 = 8100.f;
constexpr float FAST_VMAX = 1.0e6f;

#define SLAB_A_AT 1
#define SLAB_B_AT 8
#define LAG_A 99
#define H_STAGE 0
#define PF_AT 0
#define PF1_AT -1
#define ENTRY_PF 0
#define ROT_D 0
#define L2PROMO CU_TENSOR_MAP_L2_PROMOTION_L2_128B
#define KEEP_ZERO 1
#define EARLY_X 0
#define PF_ENTRY 0
constexpr int AB_STAGE = 49152;
constexpr int KV_TILE = 12288;
constexpr int D_STAGE = 28672;
constexpr int SM_SLAB = 196608;
constexpr int SM_PARAM = SM_SLAB + 20480;
constexpr int SM_RED = SM_PARAM + 4608;
constexpr int SM_BARS = SM_RED + 512;
constexpr int SMEM_BYTES = SM_BARS + 512;
constexpr int B_FULL = 0, B_EMPTY = 32, B_PREADY = 64, B_SLAB = 80, B_SLABFREE = 96, B_QKV = 104, B_KV = 112, B_KVFREE = 240, B_DFULL = 288, B_DEMPTY = 336, B_HFREE = 384;
constexpr int NB_WG = 1, NB_QKV = 6, NB_HID = 7, NB_ATT = 8, NB_HELP = 9, NB_FIN = 10, NB_LAG = 11, NB_STG = 12;

__device__ __forceinline__ void st_tagged(float2* p, float v, float tag) {
  asm volatile("{\n.reg .b64 v;\nmov.b64 v, {%1, %2};\nst.relaxed.gpu.global.b64 [%0], v;\n}" ::"l"(p), "f"(v), "f"(tag) : "memory");
}
__device__ __forceinline__ bool ld_tagged(const float2* p, float& v, float tag) {
  float tg;
  asm volatile("{\n.reg .b64 v;\nld.relaxed.gpu.global.b64 v, [%2];\nmov.b64 {%0, %1}, v;\n}" : "=f"(v), "=f"(tg) : "l"(p) : "memory");
  return __float_as_uint(tg) == __float_as_uint(tag);
}
__device__ __forceinline__ void publish(unsigned* cnt) {
  asm volatile("red.release.gpu.global.add.u32 [%0], 1;" ::"l"(cnt) : "memory");
}
__device__ __forceinline__ void wait_counter(const unsigned* cnt, unsigned target) {
  unsigned cur; int spins = 0;
  do { asm volatile("ld.acquire.gpu.global.u32 %0, [%1];" : "=r"(cur) : "l"(cnt) : "memory"); } while ((int)(cur - target) < 0 && ++spins < (1 << 22));
  asm volatile("fence.proxy.async.global;" ::: "memory");
}

__device__ __forceinline__ uint32_t exp2_pair(float ta, float tb, uint32_t one2) {
  const uint32_t v = __byte_perm(__float_as_uint(ta), __float_as_uint(tb), 0x6521);
  const uint32_t m = lop3<0xEA>(v, 0x007F007Fu, one2);
  const uint32_t q = hfma2_bf16(m, 0xBDF4BDF4u, 0x3EB43EB4u);
  const uint32_t p = hfma2_bf16(q, m, 0xBF3BBF3Bu);
  return hmul2_bf16(v, p);
}
__device__ __forceinline__ void exp_tile(const float (&s)[32], uint32_t (&p)[16], const uint32_t mask, uint32_t one2) {
  #pragma unroll
  for (int i = 0; i < 8; i++) {
    if ((mask >> i) & 1) {
      p[2 * i] = pack_bf16(ex2(s[4 * i]), ex2(s[4 * i + 1]));
      p[2 * i + 1] = pack_bf16(ex2(s[4 * i + 2]), ex2(s[4 * i + 3]));
    } else {
      p[2 * i] = exp2_pair(s[4 * i], s[4 * i + 1], one2);
      p[2 * i + 1] = exp2_pair(s[4 * i + 2], s[4 * i + 3], one2);
    }
  }
}
__device__ __forceinline__ void issue_qk(float (&s)[32], const uint32_t (&qa)[8], uint32_t klo) {
  wgmma_n64_rs(s, qa[0], qa[1], qa[2], qa[3], klo | (8u << 16), 24u, 0);
  wgmma_n64_rs(s, qa[4], qa[5], qa[6], qa[7], klo + 16u, 24u, 1);
}
__device__ __forceinline__ void issue_pv(float (&o)[12], const uint32_t (&p)[16], uint32_t vlo) {
  #pragma unroll
  for (int kk = 0; kk < 4; kk++) wgmma_n24_rs(o, p[4 * kk], p[4 * kk + 1], p[4 * kk + 2], p[4 * kk + 3], vlo + kk * 48u, 8u, 1);
}

template <int V> struct IntC { static constexpr int value = V; };
struct Maps { CUtensorMap x, wqkv, wq4, w1, sq, s1, w2, wo; };

__global__ void __launch_bounds__(640, 1)
fused_block(const __grid_constant__ Maps tm, const __nv_bfloat16* __restrict__ x, const __nv_bfloat16* __restrict__ wqkv,
            const __nv_bfloat16* __restrict__ w1, const __nv_bfloat16* __restrict__ b1,
            const __nv_bfloat16* __restrict__ w2, const __nv_bfloat16* __restrict__ wo, const __nv_bfloat16* __restrict__ b2,
            __nv_bfloat16* __restrict__ out) {
  extern __shared__ __align__(1024) uint8_t smem[];
  const uint32_t sb = smem_u32(smem);
  const uint32_t sd = sb & 0x3FFFF;
  const uint32_t bar = sb + SM_BARS;
  float* s_cs = reinterpret_cast<float*>(smem + SM_PARAM);
  float* s_cs1 = s_cs + 240;
  float* s_b1h = s_cs1 + 192;
  float4* s_row = reinterpret_cast<float4*>(smem + SM_PARAM + 2560);
  const int tid = threadIdx.x, lane = tid & 31;
  const int warp = __shfl_sync(~0u, tid >> 5, 0), wg = warp >> 2;
  const int bid = blockIdx.x, rank = bid & 1;
  const int cbA = (bid >> 1) & 7, rbA = ((bid >> 4) << 1) | rank;
  const int hd = bid >> 2, qq = bid & 3;
  const int rbD = ((bid >> 3) << 1) | rank, cbD = (bid >> 1) & 3;

  if (tid == 0) TRACE(0, 0);
  if (tid == 0) {
    for (int s = 0; s < 4; s++) { mbar_init(bar + B_FULL + 8 * s, 1); mbar_init(bar + B_EMPTY + 8 * s, 32); }
    mbar_init(bar + B_PREADY, 64); mbar_init(bar + B_PREADY + 8, 64); mbar_init(bar + B_SLAB, 1); mbar_init(bar + B_SLAB + 8, 1);
    mbar_init(bar + B_SLABFREE, 64); mbar_init(bar + B_QKV, 1); mbar_init(bar + B_HFREE, 1);
    for (int j = 0; j < 16; j++) mbar_init(bar + B_KV + 8 * j, 1);
    for (int s = 0; s < 6; s++) { mbar_init(bar + B_KVFREE + 8 * s, 32); mbar_init(bar + B_DFULL + 8 * s, 1); mbar_init(bar + B_DEMPTY + 8 * s, 16); }
    asm volatile("fence.mbarrier_init.release.cluster;" ::: "memory");
  }
  if (tid == 512) {
    asm volatile("prefetch.tensormap [%0];" ::"l"(&tm.x) : "memory");
    asm volatile("prefetch.tensormap [%0];" ::"l"(cbA < 7 ? &tm.wq4 : &tm.wqkv) : "memory");
    asm volatile("prefetch.tensormap [%0];" ::"l"(&tm.sq) : "memory");
  }
  __syncthreads();
  if (tid == 0) TRACE(0, 12);
  cluster_sync();
  if (tid == 0) TRACE(0, 13);

  if (wg == 4) {
    asm volatile("setmaxnreg.dec.sync.aligned.u32 32;");
    if (warp == 16) {
      if (lane == 0) {
        int s = 0; uint32_t ph = 1;
        const unsigned epoch_prev = __ldcg(&g_epoch);
        #pragma unroll 1
        for (int it = 0; it < 20; it++) {
          const int kb = it < 10 ? it : (it < 14 ? it - 4 : it - 14);
          mbar_wait(bar + B_EMPTY + 8 * s, ph);
          const uint32_t sa = sb + s * AB_STAGE, sw = sa + 16384, fb = bar + B_FULL + 8 * s;
          if (it < 10) {
            if (it == 0) TRACE(0, 11);
            mbar_expect(fb, it < EARLY_X ? 32768 : 16384 + 32768);
            if (it >= EARLY_X) tma_2d(sa, &tm.x, kb * 64, rbA * 128, fb);
            if (cbA < 7) tma_4d_mc(sw + rank * 16384, &tm.wq4, 0, kb * 64 + rank * 32, 0, cbA * 2, fb, 3);
            else for (int b = 0; b < 4; b++) tma_2d_mc(sw + rank * 16384 + b * 4096, &tm.wqkv, cbA * 240 + b * 64 - (b >> 1) * 8, kb * 64 + rank * 32, fb, 3);
          } else {
            mbar_expect(fb, it < 14 ? 24576 : 16384 + 24576);
            if (it >= 14) tma_2d(sa, &tm.x, kb * 64, rbA * 128, fb);
            tma_3d_mc(sw + rank * 12288, &tm.w1, 0, kb * 64 + rank * 32, cbA * 6, fb, 3);
          }
          if (PF_AT >= 0 && it == PF_AT) {
            asm volatile("cp.async.bulk.prefetch.L2.global [%0], %1;" ::"l"((const uint8_t*)x + (size_t)bid * (S_LEN * DM * 2 / 128)), "r"(S_LEN * DM * 2 / 128) : "memory");
            asm volatile("cp.async.bulk.prefetch.L2.global [%0], %1;" ::"l"((const uint8_t*)wqkv + (size_t)bid * (DM * NQKV * 2 / 128)), "r"(DM * NQKV * 2 / 128) : "memory");
          }
          if (PF1_AT >= 0 && it == PF1_AT)
            asm volatile("cp.async.bulk.prefetch.L2.global [%0], %1;" ::"l"((const uint8_t*)w1 + (size_t)bid * (DM * FF * 2 / 128)), "r"(DM * FF * 2 / 128) : "memory");
          if (it == SLAB_A_AT && bid < 120) {
            mbar_expect(bar + B_SLAB, 20480);
            for (int i = 0; i < 4; i++) tma_2d(sb + SM_SLAB + i * 5120, &tm.sq, bid * 16, i * 160, bar + B_SLAB);
          }
          if (it == SLAB_B_AT && bid < 96) {
            mbar_wait(bar + B_SLABFREE, 0);
            mbar_expect(bar + B_SLAB + 8, 20480);
            for (int i = 0; i < 4; i++) tma_2d(sb + SM_SLAB + i * 5120, &tm.s1, bid * 16, i * 160, bar + B_SLAB + 8);
          }
          if (++s == 4) { s = 0; ph ^= 1; }
        }
        const unsigned epoch = epoch_prev + 1u;
        wait_counter(&g_cnt[0], epoch * 128u);
        mbar_arrive(bar + B_QKV);
        const uint8_t* ksrc = reinterpret_cast<const uint8_t*>(g_qkv + (size_t)(NH + hd) * 256 * 192);
        const uint8_t* vsrc = reinterpret_cast<const uint8_t*>(g_qkv + (size_t)(2 * NH + hd) * 256 * 192);
        #pragma unroll 1
        for (int j = 0; j < 16; j++) {
          if ((j & 3) == 0) mbar_wait(bar + B_EMPTY + 8 * (j >> 2), ph);
          if (H_STAGE && j == 12) mbar_wait(bar + B_HFREE, 0);
          mbar_expect(bar + B_KV + 8 * j, KV_TILE);
          bulk_load(sb + j * KV_TILE, ksrc + j * 6144, 6144, bar + B_KV + 8 * j);
          bulk_load(sb + j * KV_TILE + 6144, vsrc + j * 6144, 6144, bar + B_KV + 8 * j);
        }
        if (tid == 512) TRACE(0, 9);
        asm volatile("cp.async.bulk.prefetch.L2.global [%0], %1;" ::"l"((const uint8_t*)w2 + (size_t)bid * (FF * DM * 2 / 128)), "r"(FF * DM * 2 / 128) : "memory");
        asm volatile("cp.async.bulk.prefetch.L2.global [%0], %1;" ::"l"((const uint8_t*)wo + (size_t)bid * (DM * DM * 2 / 128)), "r"(DM * DM * 2 / 128) : "memory");
        wait_counter(&g_cnt[32], epoch * 128u);
        s = 0; ph = 1;
        #pragma unroll 1
        for (int kb = 0; kb < 34; kb++) {
          if (kb == 24) {
            wait_counter(&g_cnt[64 + 32 * (rbD >> 3)], epoch * 32u);
            if (bid == 0) g_epoch = epoch;
          }
          if (kb < 6) mbar_wait(bar + B_KVFREE + 8 * s, 0); else mbar_wait(bar + B_DEMPTY + 8 * s, ph);
          const uint32_t sa = sb + s * D_STAGE, fb = bar + B_DFULL + 8 * s;
          mbar_expect(fb, D_STAGE);
          int kk = kb < 24 ? kb + ROT_D * (bid >> 3) : kb - 24 + ROT_D * (bid >> 3);
          kk = kb < 24 ? kk % 24 : kk % 10;
          const __nv_bfloat16* asrc = (kb < 24 ? g_hid + (size_t)((rbD >> 1) * 24 + kk) * 8192 : g_att + (size_t)((rbD >> 1) * 10 + kk) * 8192) + (rbD & 1) * 4096;
          bulk_load(sa, asrc, 8192, fb);
          tma_3d_mc(sa + 8192 + rank * 10240, kb < 24 ? &tm.w2 : &tm.wo, 0, kk * 64 + rank * 32, cbD * 5, fb, 3);
          if (++s == 6) { s = 0; ph ^= 1; }
        }
      }
    } else {
      if (warp == 19) {
        bar_sync(NB_QKV, 544);
        if (lane == 0) publish(&g_cnt[0]);
        __syncwarp();
        bar_sync(NB_HID, 544);
        if (lane == 0) publish(&g_cnt[32]);
        __syncwarp();
        bar_sync(NB_ATT, 544);
        if (lane == 0) publish(&g_cnt[64 + 32 * qq]);
        __syncwarp();
      } else {
        const int w = warp - 17, t64 = tid - 544;
        const float tag = __uint_as_float(__ldcg(&g_epoch) + 1u);
        float* s_red = reinterpret_cast<float*>(smem + SM_RED);
        auto slab_sum = [&](uint32_t fullbar, float2* dst) {
          mbar_wait(fullbar, 0);
          float a[8];
          #pragma unroll
          for (int i = 0; i < 8; i++) a[i] = 0.f;
          #pragma unroll 2
          for (int i = w; i < 40; i += 2) {
            const uint4 u = *reinterpret_cast<const uint4*>(smem + SM_SLAB + i * 512 + lane * 16);
            a[0] += bf_lo(u.x); a[1] += bf_hi(u.x); a[2] += bf_lo(u.y); a[3] += bf_hi(u.y);
            a[4] += bf_lo(u.z); a[5] += bf_hi(u.z); a[6] += bf_lo(u.w); a[7] += bf_hi(u.w);
          }
          #pragma unroll
          for (int i = 0; i < 4; i++) { const bool up = lane & 2; const float snd = up ? a[i] : a[i + 4]; a[i] = (up ? a[i + 4] : a[i]) + __shfl_xor_sync(~0u, snd, 2); }
          #pragma unroll
          for (int i = 0; i < 2; i++) { const bool up = lane & 4; const float snd = up ? a[i] : a[i + 2]; a[i] = (up ? a[i + 2] : a[i]) + __shfl_xor_sync(~0u, snd, 4); }
          { const bool up = lane & 8; const float snd = up ? a[0] : a[1]; a[0] = (up ? a[1] : a[0]) + __shfl_xor_sync(~0u, snd, 8); }
          a[0] += __shfl_xor_sync(~0u, a[0], 16);
          if (lane < 16) s_red[w * 16 + (lane & 1) * 8 + ((lane >> 1) & 1) * 4 + ((lane >> 2) & 1) * 2 + (lane >> 3)] = a[0];
          bar_sync(NB_HELP, 64);
          if (t64 < 16) st_tagged(dst + t64, s_red[t64] + s_red[16 + t64], tag);
          bar_sync(NB_HELP, 64);
        };
        if (bid < 120) slab_sum(bar + B_SLAB, g_colsum + bid * 16);
        mbar_arrive(bar + B_SLABFREE);
        {
          const float2* pc = g_colsum + cbA * 240 + t64;
          const int i3 = t64 < 48 ? 192 : 0;
          float c0, c1, c2, c3; bool ok; int spins = 0;
          do { ok = ld_tagged(pc, c0, tag); ok &= ld_tagged(pc + 64, c1, tag); ok &= ld_tagged(pc + 128, c2, tag); ok &= ld_tagged(pc + i3, c3, tag); } while (!ok && ++spins < (1 << 20));
          s_cs[t64] = c0; s_cs[64 + t64] = c1; s_cs[128 + t64] = c2; if (t64 < 48) s_cs[192 + t64] = c3;
        }
        {
          const float2* pr = g_rowstat + 2 * (rbA * 128 + t64);
          float m0, v0, m1, v1; bool ok; int spins = 0;
          do { ok = ld_tagged(pr, m0, tag); ok &= ld_tagged(pr + 1, v0, tag); ok &= ld_tagged(pr + 128, m1, tag); ok &= ld_tagged(pr + 129, v1, tag); } while (!ok && ++spins < (1 << 20));
          const float ra = 1.f / sqrtf(v0 + LN_EPS), rc = 1.f / sqrtf(v1 + LN_EPS);
          s_row[t64] = make_float4(m0, ra, ra / sqrtf(v0 * ra * ra + LN_EPS), 0.f);
          s_row[64 + t64] = make_float4(m1, rc, rc / sqrtf(v1 * rc * rc + LN_EPS), 0.f);
        }
        mbar_arrive(bar + B_PREADY);
        if (t64 == 0) TRACE(0, 8);
        if (bid < 96) slab_sum(bar + B_SLAB + 8, g_colsum + NQKV + bid * 16);
        {
          const float e0 = __bfloat162float(b1[cbA * 192 + t64]), e1 = __bfloat162float(b1[cbA * 192 + 64 + t64]), e2 = __bfloat162float(b1[cbA * 192 + 128 + t64]);
          const float2* pc = g_colsum + NQKV + cbA * 192 + t64;
          float c0, c1, c2; bool ok; int spins = 0;
          do { ok = ld_tagged(pc, c0, tag); ok &= ld_tagged(pc + 64, c1, tag); ok &= ld_tagged(pc + 128, c2, tag); } while (!ok && ++spins < (1 << 20));
          s_cs1[t64] = c0; s_cs1[64 + t64] = c1; s_cs1[128 + t64] = c2;
          s_b1h[t64] = 0.5f * e0; s_b1h[64 + t64] = 0.5f * e1; s_b1h[128 + t64] = 0.5f * e2;
        }
        mbar_arrive(bar + B_PREADY + 8);
        if (t64 == 0) TRACE(0, 10);
      }
    }
    cluster_sync();
    return;
  }

  asm volatile("setmaxnreg.inc.sync.aligned.u32 112;");
  const int w4 = warp & 3, g = lane >> 2, t = lane & 3;
  const int mi = wg & 1, ni = wg >> 1;
  {
    const float tag = __uint_as_float(__ldcg(&g_epoch) + 1u);
    const int row = bid * 16 + warp;
    const uint2* px = reinterpret_cast<const uint2*>(x + (size_t)row * DM);
    float v[20], sum = 0.f, sq = 0.f;
    #pragma unroll
    for (int i = 0; i < 5; i++) {
      const uint2 u = __ldg(px + i * 32 + lane);
      v[4 * i] = bf_lo(u.x); v[4 * i + 1] = bf_hi(u.x); v[4 * i + 2] = bf_lo(u.y); v[4 * i + 3] = bf_hi(u.y);
      sum += (v[4 * i] + v[4 * i + 1]) + (v[4 * i + 2] + v[4 * i + 3]);
    }
    #pragma unroll
    for (int o = 16; o; o >>= 1) sum += __shfl_xor_sync(~0u, sum, o);
    const float mean = sum * (1.f / DM);
    #pragma unroll
    for (int i = 0; i < 20; i++) { const float d = v[i] - mean; sq = fmaf(d, d, sq); }
    #pragma unroll
    for (int o = 16; o; o >>= 1) sq += __shfl_xor_sync(~0u, sq, o);
    if (lane < 2) st_tagged(g_rowstat + 2 * row + lane, lane ? sq * (1.f / DM) : mean, tag);
  }
  int s = 0; uint32_t ph = 0;
  const int tg0 = rbA * 16 + mi * 8 + w4 * 2;
  {
    float acc[60];
    #pragma unroll 1
    for (int kb = 0; kb < 10; kb++) {
      if (kb == LAG_A && ni == 1) bar_sync(NB_LAG, 512);
      mbar_wait(bar + B_FULL + 8 * s, ph);
      if (tid == 0 && kb == 0) TRACE(0, 1);
      const uint32_t alo = ((sd + s * AB_STAGE + mi * 8192) >> 4) | (1u << 16);
      const uint32_t blo = ((sd + s * AB_STAGE + 16384 + ni * 8192) >> 4) | (256u << 16);
      wg_fence();
      #pragma unroll
      for (int k = 0; k < 4; k++) wgmma_n120_ss(acc, alo + k * 2, 64u | (1u << 30), blo + (k >> 1) * 1024 + (k & 1) * 128, 64u | (1u << 30), (kb | k) != 0);
      wg_commit();
      if (LAG_A < 10 && kb == 9 && ni == 0) asm volatile("bar.arrive %0, 512;" ::"n"(NB_LAG) : "memory");
      if (kb > 0) { wg_wait<1>(); if (lane < 2) mbar_arrive_cta(bar + B_EMPTY + 8 * ((s + 3) & 3), lane); }
      if (++s == 4) { s = 0; ph ^= 1; }
    }
    wg_wait<0>();
    if (lane < 2) mbar_arrive_cta(bar + B_EMPTY + 8 * ((s + 3) & 3), lane);
    if (tid == 0) TRACE(0, 2); if (tid == 384) TRACE(1, 8);
    mbar_wait(bar + B_PREADY, 0);
    const float4 st0 = s_row[mi * 64 + w4 * 16 + g], st1 = s_row[mi * 64 + w4 * 16 + g + 8];
    const float nm0 = -st0.x, nm1 = -st1.x;
    uint32_t* dbase = reinterpret_cast<uint32_t*>(g_qkv + ((size_t)(cbA * 12 + ni * 6) * 256 + tg0) * 192) + lane;
    const uint32_t kaug0 = ((MUFU_MASK >> (tg0 & 15)) & 1) ? 0u : 0x3B8043C0u;
    const uint32_t kaug1 = ((MUFU_MASK >> ((tg0 + 1) & 15)) & 1) ? 0u : 0x3B8043C0u;
    #pragma unroll
    for (int pi = 0; pi < 3; pi++) {
      const int P = cbA * 6 + ni * 3 + pi, sec = P >> 4;
      const float sc = sec == 0 ? QSCALE : 1.f;
      const float r0 = st0.y * sc, r1 = st1.y * sc;
      uint32_t* de = dbase + pi * 2 * 256 * 96;
      uint32_t* dod = de + 256 * 96;
      uint32_t w[5][2];
      #pragma unroll
      for (int gi = 0; gi < 5; gi++) {
        const int i = pi * 5 + gi;
        const float2 cs = *reinterpret_cast<const float2*>(s_cs + ni * 120 + 8 * i + 2 * t);
        w[gi][0] = pack_bf16(fmaf(nm0, cs.x, acc[4 * i]) * r0, fmaf(nm0, cs.y, acc[4 * i + 1]) * r0);
        w[gi][1] = pack_bf16(fmaf(nm1, cs.x, acc[4 * i + 2]) * r1, fmaf(nm1, cs.y, acc[4 * i + 3]) * r1);
      }
      const uint32_t aug0 = sec == 1 ? kaug0 : (sec == 0 ? 0x3F803F80u : 0x00003F80u);
      const uint32_t aug1 = sec == 1 ? kaug1 : (sec == 0 ? 0x3F803F80u : 0x00003F80u);
      const uint32_t ae0 = t == 2 ? aug0 : 0u, ae1 = t == 2 ? aug1 : 0u, ao0 = t == 0 ? aug0 : 0u, ao1 = t == 0 ? aug1 : 0u;
      de[0] = w[0][0];  de[96] = w[0][1];  de[32] = w[1][0];  de[96 + 32] = w[1][1];
      de[64] = t < 2 ? w[2][0] : ae0;   de[96 + 64] = t < 2 ? w[2][1] : ae1;
      dod[0] = w[3][0]; dod[96] = w[3][1]; dod[32] = w[4][0]; dod[96 + 32] = w[4][1];
      dod[64] = t >= 2 ? w[2][0] : ao0; dod[96 + 64] = t >= 2 ? w[2][1] : ao1;
      if (sec == 1) {
        uint32_t e0 = hfma2_bf16(w[1][0], w[1][0], hmul2_bf16(w[0][0], w[0][0])), e1 = hfma2_bf16(w[1][1], w[1][1], hmul2_bf16(w[0][1], w[0][1]));
        uint32_t o0 = hfma2_bf16(w[4][0], w[4][0], hmul2_bf16(w[3][0], w[3][0])), o1 = hfma2_bf16(w[4][1], w[4][1], hmul2_bf16(w[3][1], w[3][1]));
        if (t < 2) { e0 = hfma2_bf16(w[2][0], w[2][0], e0); e1 = hfma2_bf16(w[2][1], w[2][1], e1); }
        else       { o0 = hfma2_bf16(w[2][0], w[2][0], o0); o1 = hfma2_bf16(w[2][1], w[2][1], o1); }
        float fe0 = bf_lo(e0) + bf_hi(e0), fe1 = bf_lo(e1) + bf_hi(e1), fo0 = bf_lo(o0) + bf_hi(o0), fo1 = bf_lo(o1) + bf_hi(o1);
        #pragma unroll
        for (int o = 1; o < 4; o <<= 1) {
          fe0 += __shfl_xor_sync(~0u, fe0, o); fe1 += __shfl_xor_sync(~0u, fe1, o); fo0 += __shfl_xor_sync(~0u, fo0, o); fo1 += __shfl_xor_sync(~0u, fo1, o);
        }
        const unsigned me = __reduce_max_sync(~0u, max(__float_as_uint(fe0) & 0x7FFFFFFFu, __float_as_uint(fe1) & 0x7FFFFFFFu));
        const unsigned mo = __reduce_max_sync(~0u, max(__float_as_uint(fo0) & 0x7FFFFFFFu, __float_as_uint(fo1) & 0x7FFFFFFFu));
        if (lane == 0) { float* kn = g_knorm + (size_t)(2 * P - 32) * 128 + (tg0 >> 1); kn[0] = __uint_as_float(me); kn[128] = __uint_as_float(mo); }
      } else if (sec == 2) {
        unsigned m = 0;
        #pragma unroll
        for (int gi = 0; gi < 5; gi++) m = __vmaxu2(m, __vmaxu2(w[gi][0] & 0x7FFF7FFFu, w[gi][1] & 0x7FFF7FFFu));
        m = __reduce_max_sync(~0u, max(m << 16, m & 0xFFFF0000u));
        if (lane == 0) { float* vm = g_vmax + (size_t)(2 * P - 64) * 128 + (tg0 >> 1); vm[0] = __uint_as_float(m); vm[128] = __uint_as_float(m); }
      }
    }
    asm volatile("bar.arrive %0, 544;" ::"n"(NB_QKV) : "memory");
  }
  if (tid == 0) TRACE(0, 4); if (tid == 384) TRACE(1, 9);
  uint32_t qa[8];
  unsigned kmax_bits, vmax_bits;
  auto load_q = [&](int tg) {
    const uint32_t* qp = reinterpret_cast<const uint32_t*>(g_qkv + ((size_t)hd * 256 + tg) * 192) + lane;
    qa[0] = __ldcg(qp); qa[1] = __ldcg(qp + 96); qa[2] = __ldcg(qp + 32); qa[3] = __ldcg(qp + 96 + 32);
    qa[4] = __ldcg(qp + 64); qa[5] = __ldcg(qp + 96 + 64); qa[6] = 0; qa[7] = 0;
    asm volatile("" : "+r"(qa[6]), "+r"(qa[7]));
  };
  {
    float acc[48];
    #pragma unroll 1
    for (int kb = 0; kb < 10; kb++) {
      mbar_wait(bar + B_FULL + 8 * s, ph);
      const uint32_t alo = ((sd + s * AB_STAGE + mi * 8192) >> 4) | (1u << 16);
      const uint32_t blo = ((sd + s * AB_STAGE + 16384 + ni * 3 * 2048) >> 4) | (128u << 16);
      wg_fence();
      #pragma unroll
      for (int k = 0; k < 4; k++) wgmma_n96_ss(acc, alo + k * 2, 64u | (1u << 30), blo + (k >> 1) * 768 + (k & 1) * 64, 32u | (2u << 30), (kb | k) != 0);
      wg_commit();
      if (kb > 0) { wg_wait<1>(); if (lane < 2) mbar_arrive_cta(bar + B_EMPTY + 8 * ((s + 3) & 3), lane); }
      if (++s == 4) { s = 0; ph ^= 1; }
    }
    wg_wait<0>();
    if (lane < 2) mbar_arrive_cta(bar + B_EMPTY + 8 * ((s + 3) & 3), lane);
    if (tid == 0) TRACE(0, 5); if (tid == 384) TRACE(1, 10);
    mbar_wait(bar + B_QKV, 0);
    load_q(qq * 64 + wg * 16 + w4 * 2);
    const float4 kn4 = __ldcg(reinterpret_cast<const float4*>(g_knorm + hd * 128) + lane), vm4 = __ldcg(reinterpret_cast<const float4*>(g_vmax + hd * 128) + lane);
    kmax_bits = max(max(__float_as_uint(kn4.x), __float_as_uint(kn4.y)), max(__float_as_uint(kn4.z), __float_as_uint(kn4.w)));
    vmax_bits = max(max(__float_as_uint(vm4.x), __float_as_uint(vm4.y)), max(__float_as_uint(vm4.z), __float_as_uint(vm4.w)));
    mbar_wait(bar + B_PREADY + 8, 0);
    const float4 st0 = s_row[mi * 64 + w4 * 16 + g], st1 = s_row[mi * 64 + w4 * 16 + g + 8];
    const float nm0 = -st0.x, nm1 = -st1.x, a0 = 0.5f * st0.z, a1 = 0.5f * st1.z;
    uint32_t* dst = reinterpret_cast<uint32_t*>(g_hid + ((size_t)(rbA * 24 + cbA * 3) * 16 + mi * 8 + w4 * 2) * 512) + lane;
    constexpr float GA = 1.5957691216057308f, GB = 1.5957691216057308f * 0.044715f * 4.f;
    #pragma unroll
    for (int i = 0; i < 12; i++) {
      const float2 cs = *reinterpret_cast<const float2*>(s_cs1 + ni * 96 + 8 * i + 2 * t);
      const float2 bb = *reinterpret_cast<const float2*>(s_b1h + ni * 96 + 8 * i + 2 * t);
      float h[4];
      h[0] = fmaf(fmaf(nm0, cs.x, acc[4 * i]), a0, bb.x);     h[1] = fmaf(fmaf(nm0, cs.y, acc[4 * i + 1]), a0, bb.y);
      h[2] = fmaf(fmaf(nm1, cs.x, acc[4 * i + 2]), a1, bb.x); h[3] = fmaf(fmaf(nm1, cs.y, acc[4 * i + 3]), a1, bb.y);
      #pragma unroll
      for (int e = 0; e < 4; e++) {
        const float u = h[e] * fmaf(h[e] * h[e], GB, GA);
        h[e] = fmaf(h[e], tanh_fast(u), h[e]);
      }
      const int kgl = ni * 12 + i;
      uint32_t* d = dst + (kgl >> 3) * 4096 + (kgl & 7) * 32;
      d[0] = pack_bf16(h[0], h[1]);
      d[256] = pack_bf16(h[2], h[3]);
    }
    asm volatile("bar.arrive %0, 544;" ::"n"(NB_HID) : "memory");
  }
  if (tid == 0) TRACE(0, 6); if (tid == 384) TRACE(1, 11);
  {
    const float kmax2 = __uint_as_float(__reduce_max_sync(~0u, kmax_bits)), vmax = __uint_as_float(__reduce_max_sync(~0u, vmax_bits));
    const bool odd = hd & 1;
    const uint32_t kv0 = sd >> 4, bb = bar + B_KV;
    constexpr uint32_t TB = KV_TILE >> 4, VOFF = (6144 >> 4) + (24u << 16);
    constexpr uint32_t FREE_MASK = (1u << 2) | (1u << 4) | (1u << 6) | (1u << 9) | (1u << 11) | (1u << 13);
    uint32_t one2 = 0x3F803F80u;
    asm volatile("" : "+r"(one2));

    #pragma unroll 1
    for (int r = 0; r < 2; r++) {
      const int tg = qq * 64 + wg * 16 + r * 8 + w4 * 2;
      if (r == 1) load_q(tg);
      const bool real2 = odd ? (t >= 2) : (t < 2);
      float n0 = bf_lo(qa[0]) * bf_lo(qa[0]) + bf_hi(qa[0]) * bf_hi(qa[0]) + bf_lo(qa[2]) * bf_lo(qa[2]) + bf_hi(qa[2]) * bf_hi(qa[2]);
      float n1 = bf_lo(qa[1]) * bf_lo(qa[1]) + bf_hi(qa[1]) * bf_hi(qa[1]) + bf_lo(qa[3]) * bf_lo(qa[3]) + bf_hi(qa[3]) * bf_hi(qa[3]);
      if (real2) { n0 += bf_lo(qa[4]) * bf_lo(qa[4]) + bf_hi(qa[4]) * bf_hi(qa[4]); n1 += bf_lo(qa[5]) * bf_lo(qa[5]) + bf_hi(qa[5]) * bf_hi(qa[5]); }
      n0 += __shfl_xor_sync(~0u, n0, 1); n0 += __shfl_xor_sync(~0u, n0, 2);
      n1 += __shfl_xor_sync(~0u, n1, 1); n1 += __shfl_xor_sync(~0u, n1, 2);
      const bool ok = (n0 * kmax2 * 1.06f <= FAST_BOUND2) && (n1 * kmax2 * 1.06f <= FAST_BOUND2) && (vmax <= FAST_VMAX);
      int allok;
      asm volatile("{\n.reg .pred p, q;\nsetp.ne.b32 p, %1, 0;\nbarrier.red.and.pred q, %2, 128, p;\nselp.b32 %0, 1, 0, q;\n}" : "=r"(allok) : "r"((int)ok), "r"(NB_WG + wg) : "memory");
      allok = __shfl_sync(~0u, allok, 0);
      float o[12];
      #pragma unroll
      for (int i = 0; i < 12; i++) o[i] = 0.f;
      int freed = 0;
      if (allok) {
        float s0[32], s1[32]; uint32_t p[16];
        if (r == 0) mbar_wait(bb, 0);
        if (tid == 0) TRACE(1, 2 + r); if (tid == 384) TRACE(1, 12 + r);
        wg_fence(); issue_qk(s0, qa, kv0); wg_commit(); wg_wait<0>();
        #pragma unroll 1
        for (int j = 0; j < 16; j++) {
          const uint32_t base = kv0 + j * TB;
          wg_fence(); issue_qk(s1, qa, base + 192u); wg_commit();
          exp_tile(s0, p, MUFU_MASK & 0xFF, one2);
          wg_fence(); issue_pv(o, p, base + VOFF); wg_commit();
          if (r == 0 && j < 15) mbar_wait(bb + (j + 1) * 8, 0);
          wg_wait<0>();
          wg_fence(); issue_qk(s0, qa, j < 15 ? base + TB : base); wg_commit();
          exp_tile(s1, p, MUFU_MASK >> 8, one2);
          wg_fence(); issue_pv(o, p, base + VOFF + 4 * 48u); wg_commit();
          wg_wait<0>();
          if (r == 1 && ((FREE_MASK >> j) & 1)) { if (lane < 2) mbar_arrive_cta(bar + B_KVFREE + 8 * freed, lane); freed++; }
        }
      } else {
        if (!real2) { qa[4] = 0; qa[5] = 0; }
        float m0 = -INFINITY, m1 = -INFINITY;
        float sc[32]; uint32_t p[16];
        #pragma unroll 1
        for (int u = 0; u < 32; u++) {
          const uint32_t base = kv0 + (u >> 1) * TB;
          mbar_wait(bb + (u >> 1) * 8, 0);
          wg_fence(); issue_qk(sc, qa, base + (u & 1) * 192u); wg_commit(); wg_wait<0>();
          float x0 = m0, x1 = m1;
          #pragma unroll
          for (int i = 0; i < 8; i++) { x0 = fmaxf(x0, fmaxf(sc[4 * i], sc[4 * i + 1])); x1 = fmaxf(x1, fmaxf(sc[4 * i + 2], sc[4 * i + 3])); }
          x0 = fmaxf(x0, __shfl_xor_sync(~0u, x0, 1)); x0 = fmaxf(x0, __shfl_xor_sync(~0u, x0, 2));
          x1 = fmaxf(x1, __shfl_xor_sync(~0u, x1, 1)); x1 = fmaxf(x1, __shfl_xor_sync(~0u, x1, 2));
          const float c0 = ex2(m0 - x0), c1 = ex2(m1 - x1);
          m0 = x0; m1 = x1;
          #pragma unroll
          for (int i = 0; i < 3; i++) { o[4 * i] *= c0; o[4 * i + 1] *= c0; o[4 * i + 2] *= c1; o[4 * i + 3] *= c1; }
          #pragma unroll
          for (int i = 0; i < 8; i++) {
            p[2 * i] = pack_bf16(ex2(sc[4 * i] - m0), ex2(sc[4 * i + 1] - m0));
            p[2 * i + 1] = pack_bf16(ex2(sc[4 * i + 2] - m1), ex2(sc[4 * i + 3] - m1));
          }
          wg_fence(); issue_pv(o, p, base + VOFF + (u & 1) * 4 * 48u); wg_commit(); wg_wait<0>();
        }
        if (r == 1 && lane < 2) for (int i = 0; i < 6; i++) mbar_arrive_cta(bar + B_KVFREE + 8 * i, lane);
      }
      const int src = (lane & ~3) | (odd ? 0 : 2);
      const float i0 = 1.f / __shfl_sync(~0u, o[8], src), i1 = 1.f / __shfl_sync(~0u, o[10], src);
      const int kg0 = (20 * hd) >> 3;
      uint32_t* ob = reinterpret_cast<uint32_t*>(g_att + ((size_t)(tg >> 4) * 10 * 16 + (tg & 15)) * 512) + lane;
      auto kaddr = [&](int kg) { return ob + (kg >> 3) * 4096 + (kg & 7) * 32; };
      uint32_t* d0 = kaddr(odd ? kg0 + 1 : kg0);
      uint32_t* d1 = kaddr(odd ? kg0 + 2 : kg0 + 1);
      uint32_t* d2 = kaddr(odd ? kg0 : kg0 + 2);
      d0[0] = pack_bf16(o[0] * i0, o[1] * i0); d0[256] = pack_bf16(o[2] * i1, o[3] * i1);
      d1[0] = pack_bf16(o[4] * i0, o[5] * i0); d1[256] = pack_bf16(o[6] * i1, o[7] * i1);
      if (real2) { d2[0] = pack_bf16(o[8] * i0, o[9] * i0); d2[256] = pack_bf16(o[10] * i1, o[11] * i1); }
    }
    asm volatile("bar.arrive %0, 544;" ::"n"(NB_ATT) : "memory");
  }
  if (tid == 0) TRACE(1, 4); if (tid == 384) TRACE(1, 14);
  auto phase_d = [&](auto nseg_c, auto mma, auto& acc) {
    constexpr int NSEG = decltype(nseg_c)::value;
    constexpr int NIT = NSEG / 2;
    const int col0 = cbD * 160 + wg * 96, row0 = rbD * 64 + w4 * 16;
    uint4 xv[NIT];
    #pragma unroll
    for (int it = 0; it < NIT; it++) {
      const int idx = it * 32 + lane, r = idx / NSEG, c8 = idx % NSEG;
      xv[it] = __ldg(reinterpret_cast<const uint4*>(x + (size_t)(row0 + r) * DM + col0 + c8 * 8));
    }
    int sD = 0; uint32_t phD = 0;
    #pragma unroll 1
    for (int kb = 0; kb < 34; kb++) {
      mbar_wait(bar + B_DFULL + 8 * sD, phD);
      if (tid == 0 && kb == 0) TRACE(2, 1);
      if (tid == 0 && kb == 24) TRACE(2, 2);
      const uint32_t alo = ((sd + sD * D_STAGE) >> 4) | (8u << 16);
      const uint32_t blo = ((sd + sD * D_STAGE + 8192 + wg * 3 * 2048) >> 4) | (128u << 16);
      wg_fence();
      #pragma unroll
      for (int k = 0; k < 4; k++) mma(acc, alo + k * 16, blo + (k >> 1) * 640 + (k & 1) * 64, (kb | k) != 0);
      wg_commit();
      if (kb > 0) { wg_wait<1>(); if (lane < 2) mbar_arrive_cta(bar + B_DEMPTY + 8 * (sD == 0 ? 5 : sD - 1), lane); }
      if (++sD == 6) { sD = 0; phD ^= 1; }
    }
    wg_wait<0>();
    if (tid == 0) TRACE(2, 3);
    float* stg = reinterpret_cast<float*>(smem) + warp * (16 * 100);
    uint4 bv[NIT];
    #pragma unroll
    for (int it = 0; it < NIT; it++) bv[it] = __ldg(reinterpret_cast<const uint4*>(b2 + col0 + ((it * 32 + lane) % NSEG) * 8));
    bar_sync(NB_FIN, 256);
    #pragma unroll
    for (int i = 0; i < NSEG; i++) {
      *reinterpret_cast<float2*>(stg + g * 100 + 8 * i + 2 * t) = make_float2(acc[4 * i], acc[4 * i + 1]);
      *reinterpret_cast<float2*>(stg + (g + 8) * 100 + 8 * i + 2 * t) = make_float2(acc[4 * i + 2], acc[4 * i + 3]);
    }
    __syncwarp();
    #pragma unroll
    for (int it = 0; it < NIT; it++) {
      const int idx = it * 32 + lane, r = idx / NSEG, c8 = idx % NSEG;
      const float4 a0 = *reinterpret_cast<const float4*>(stg + r * 100 + c8 * 8), a1 = *reinterpret_cast<const float4*>(stg + r * 100 + c8 * 8 + 4);
      uint4 o;
      o.x = pack_bf16(a0.x + bf_lo(bv[it].x) + bf_lo(xv[it].x), a0.y + bf_hi(bv[it].x) + bf_hi(xv[it].x));
      o.y = pack_bf16(a0.z + bf_lo(bv[it].y) + bf_lo(xv[it].y), a0.w + bf_hi(bv[it].y) + bf_hi(xv[it].y));
      o.z = pack_bf16(a1.x + bf_lo(bv[it].z) + bf_lo(xv[it].z), a1.y + bf_hi(bv[it].z) + bf_hi(xv[it].z));
      o.w = pack_bf16(a1.z + bf_lo(bv[it].w) + bf_lo(xv[it].w), a1.w + bf_hi(bv[it].w) + bf_hi(xv[it].w));
      *reinterpret_cast<uint4*>(out + (size_t)(row0 + r) * DM + col0 + c8 * 8) = o;
    }
    if (tid == 0) TRACE(2, 4);
  };
  if (wg == 0) {
    float acc[48];
    phase_d(IntC<12>{}, [](float (&a)[48], uint32_t da, uint32_t db, int sc) { wgmma_n96_ss(a, da, 64u, db, 32u | (2u << 30), sc); }, acc);
  } else if (wg == 1) {
    float acc[32];
    phase_d(IntC<8>{}, [](float (&a)[32], uint32_t da, uint32_t db, int sc) { wgmma_n64_ss(a, da, 64u, db, 32u | (2u << 30), sc); }, acc);
  }
  cluster_sync();
}

typedef CUresult (*EncodeTiledFn)(CUtensorMap*, CUtensorMapDataType, cuuint32_t, void*, const cuuint64_t*, const cuuint64_t*, const cuuint32_t*,
                                  const cuuint32_t*, CUtensorMapInterleave, CUtensorMapSwizzle, CUtensorMapL2promotion, CUtensorMapFloatOOBfill);

CUtensorMap make_map(EncodeTiledFn fn, const void* base, int rank, const cuuint64_t* dims, const cuuint64_t* strides, const cuuint32_t* box, CUtensorMapSwizzle sw) {
  CUtensorMap m;
  const cuuint32_t es[4] = {1, 1, 1, 1};
  CUresult rc = fn(&m, CU_TENSOR_MAP_DATA_TYPE_BFLOAT16, rank, const_cast<void*>(base), dims, strides, box, es, CU_TENSOR_MAP_INTERLEAVE_NONE, sw,
                   L2PROMO, CU_TENSOR_MAP_FLOAT_OOB_FILL_NONE);
  (void)rc;
  return m;
}

}

extern "C" void kernel_launch(void* const* d_in, const int* in_sizes, int n_in, void* d_out, int out_size) {
  const __nv_bfloat16* x = static_cast<const __nv_bfloat16*>(d_in[0]);
  const __nv_bfloat16* wqkv = static_cast<const __nv_bfloat16*>(d_in[1]);
  const __nv_bfloat16* wo = static_cast<const __nv_bfloat16*>(d_in[2]);
  const __nv_bfloat16* w1 = static_cast<const __nv_bfloat16*>(d_in[4]);
  const __nv_bfloat16* b1 = static_cast<const __nv_bfloat16*>(d_in[5]);
  const __nv_bfloat16* w2 = static_cast<const __nv_bfloat16*>(d_in[6]);
  const __nv_bfloat16* b2 = static_cast<const __nv_bfloat16*>(d_in[7]);
  __nv_bfloat16* out = static_cast<__nv_bfloat16*>(d_out);

  static EncodeTiledFn encode = nullptr;
  if (!encode) {
    void* fn = nullptr;
    cudaDriverEntryPointQueryResult qr;
    cudaGetDriverEntryPoint("cuTensorMapEncodeTiled", &fn, cudaEnableDefault, &qr);
    encode = reinterpret_cast<EncodeTiledFn>(fn);
    cudaFuncSetAttribute(fused_block, cudaFuncAttributeMaxDynamicSharedMemorySize, SMEM_BYTES);
  }
  Maps tm;
  { const cuuint64_t d[2] = {DM, S_LEN}, st[1] = {DM * 2}; const cuuint32_t b[2] = {64, 128}; tm.x = make_map(encode, x, 2, d, st, b, CU_TENSOR_MAP_SWIZZLE_128B); }
  { const cuuint64_t d[2] = {NQKV, DM}, st[1] = {NQKV * 2}; const cuuint32_t b[2] = {64, 32}; tm.wqkv = make_map(encode, wqkv, 2, d, st, b, CU_TENSOR_MAP_SWIZZLE_128B); }
  { const cuuint64_t d[4] = {64, DM, 2, 16}, st[3] = {NQKV * 2, 128, 240}; const cuuint32_t b[4] = {64, 32, 2, 2}; tm.wq4 = make_map(encode, wqkv, 4, d, st, b, CU_TENSOR_MAP_SWIZZLE_128B); }
  { const cuuint64_t d[3] = {32, DM, FF / 32}, st[2] = {FF * 2, 64}; const cuuint32_t b[3] = {32, 32, 6}; tm.w1 = make_map(encode, w1, 3, d, st, b, CU_TENSOR_MAP_SWIZZLE_64B); }
  { const cuuint64_t d[2] = {NQKV, DM}, st[1] = {NQKV * 2}; const cuuint32_t b[2] = {16, 160}; tm.sq = make_map(encode, wqkv, 2, d, st, b, CU_TENSOR_MAP_SWIZZLE_NONE); }
  { const cuuint64_t d[2] = {FF, DM}, st[1] = {FF * 2}; const cuuint32_t b[2] = {16, 160}; tm.s1 = make_map(encode, w1, 2, d, st, b, CU_TENSOR_MAP_SWIZZLE_NONE); }
  { const cuuint64_t d[3] = {32, FF, DM / 32}, st[2] = {DM * 2, 64}; const cuuint32_t b[3] = {32, 32, 5}; tm.w2 = make_map(encode, w2, 3, d, st, b, CU_TENSOR_MAP_SWIZZLE_64B); }
  { const cuuint64_t d[3] = {32, DM, DM / 32}, st[2] = {DM * 2, 64}; const cuuint32_t b[3] = {32, 32, 5}; tm.wo = make_map(encode, wo, 3, d, st, b, CU_TENSOR_MAP_SWIZZLE_64B); }

  cudaLaunchAttribute at[1];
  at[0].id = cudaLaunchAttributeClusterDimension; at[0].val.clusterDim.x = 2; at[0].val.clusterDim.y = 1; at[0].val.clusterDim.z = 1;
  cudaLaunchConfig_t cfg = {};
  cfg.stream = cudaStreamPerThread;
  cfg.gridDim = dim3(128); cfg.blockDim = dim3(640); cfg.dynamicSmemBytes = SMEM_BYTES; cfg.attrs = at; cfg.numAttrs = 1;
  cudaLaunchKernelEx(&cfg, fused_block, tm, x, wqkv, w1, b1, w2, wo, b2, out);
}
```

```cpp
#include <cuda_runtime.h>
#include <cuda_bf16.h>
#include <cuda.h>
#include <stdint.h>

namespace {

constexpr int S_LEN = 2048, DM = 640, NH = 32, FF = 1536, NQKV = 1920;
constexpr float LN_EPS = 1e-5f;

__device__ __align__(1024) __nv_bfloat16 g_qkv[3 * NH * 256 * 192];
__device__ __align__(1024) __nv_bfloat16 g_hid[16 * 24 * 8192];
__device__ __align__(1024) __nv_bfloat16 g_att[16 * 10 * 8192];
__device__ float2 g_rowstat[2 * S_LEN];
__device__ float2 g_colsum[NQKV + FF];
__device__ float g_knorm[NH * 128];
__device__ float g_vmax[NH * 128];
__device__ unsigned g_epoch;
__device__ unsigned g_cnt[6 * 32];


__device__ __forceinline__ uint32_t smem_u32(const void* p) { return (uint32_t)__cvta_generic_to_shared(p); }
__device__ __forceinline__ void wg_fence() { asm volatile("wgmma.fence.sync.aligned;" ::: "memory"); }
__device__ __forceinline__ void wg_commit() { asm volatile("wgmma.commit_group.sync.aligned;" ::: "memory"); }
template <int N> __device__ __forceinline__ void wg_wait() { asm volatile("wgmma.wait_group.sync.aligned %0;" ::"n"(N) : "memory"); }
__device__ __forceinline__ void mbar_init(uint32_t bar, int cnt) { asm volatile("mbarrier.init.shared::cta.b64 [%0], %1;" ::"r"(bar), "r"(cnt)); }
__device__ __forceinline__ void mbar_expect(uint32_t bar, uint32_t bytes) {
  asm volatile("mbarrier.arrive.expect_tx.shared::cta.b64 _, [%0], %1;" ::"r"(bar), "r"(bytes) : "memory");
}
__device__ __forceinline__ void mbar_arrive(uint32_t bar) { asm volatile("mbarrier.arrive.shared::cta.b64 _, [%0];" ::"r"(bar) : "memory"); }
__device__ __forceinline__ void mbar_arrive_cta(uint32_t bar, uint32_t cta) {
  asm volatile("{\n.reg .b32 r;\nmapa.shared::cluster.u32 r, %0, %1;\nmbarrier.arrive.shared::cluster.b64 _, [r];\n}" ::"r"(bar), "r"(cta) : "memory");
}
__device__ __forceinline__ void mbar_wait(uint32_t bar, uint32_t parity) {
  asm volatile("{\n.reg .pred p;\nWAIT:\nmbarrier.try_wait.parity.shared::cta.b64 p, [%0], %1;\n@p bra DONE;\nbra WAIT;\nDONE:\n}" ::"r"(bar), "r"(parity) : "memory");
}
__device__ __forceinline__ void bulk_load(uint32_t dst, const void* src, uint32_t bytes, uint32_t bar) {
  asm volatile("cp.async.bulk.shared::cluster.global.mbarrier::complete_tx::bytes [%0], [%1], %2, [%3];" ::"r"(dst), "l"(src), "r"(bytes), "r"(bar) : "memory");
}
__device__ __forceinline__ void tma_2d(uint32_t dst, const CUtensorMap* tm, int c0, int c1, uint32_t bar) {
  asm volatile("cp.async.bulk.tensor.2d.shared::cluster.global.mbarrier::complete_tx::bytes [%0], [%1, {%3, %4}], [%2];" ::"r"(dst), "l"(tm), "r"(bar), "r"(c0), "r"(c1) : "memory");
}
__device__ __forceinline__ void tma_2d_mc(uint32_t dst, const CUtensorMap* tm, int c0, int c1, uint32_t bar, uint16_t mask) {
  asm volatile("cp.async.bulk.tensor.2d.shared::cluster.global.mbarrier::complete_tx::bytes.multicast::cluster [%0], [%1, {%3, %4}], [%2], %5;" ::"r"(dst), "l"(tm), "r"(bar), "r"(c0), "r"(c1), "h"(mask) : "memory");
}
__device__ __forceinline__ void tma_3d_mc(uint32_t dst, const CUtensorMap* tm, int c0, int c1, int c2, uint32_t bar, uint16_t mask) {
  asm volatile("cp.async.bulk.tensor.3d.shared::cluster.global.mbarrier::complete_tx::bytes.multicast::cluster [%0], [%1, {%3, %4, %5}], [%2], %6;" ::"r"(dst), "l"(tm), "r"(bar), "r"(c0), "r"(c1), "r"(c2), "h"(mask) : "memory");
}
__device__ __forceinline__ void tma_4d_mc(uint32_t dst, const CUtensorMap* tm, int c0, int c1, int c2, int c3, uint32_t bar, uint16_t mask) {
  asm volatile("cp.async.bulk.tensor.4d.shared::cluster.global.mbarrier::complete_tx::bytes.multicast::cluster [%0], [%1, {%3, %4, %5, %6}], [%2], %7;" ::"r"(dst), "l"(tm), "r"(bar), "r"(c0), "r"(c1), "r"(c2), "r"(c3), "h"(mask) : "memory");
}
__device__ __forceinline__ void cluster_sync() { asm volatile("barrier.cluster.arrive.relaxed.aligned;\nbarrier.cluster.wait.aligned;" ::: "memory"); }
__device__ __forceinline__ void bar_sync(int id, int n) { asm volatile("bar.sync %0, %1;" ::"r"(id), "r"(n) : "memory"); }
__device__ __forceinline__ float ex2(float x) { float y; asm("ex2.approx.ftz.f32 %0, %1;" : "=f"(y) : "f"(x)); return y; }
__device__ __forceinline__ float tanh_fast(float x) { float y; asm("tanh.approx.f32 %0, %1;" : "=f"(y) : "f"(x)); return y; }
__device__ __forceinline__ uint32_t pack_bf16(float lo, float hi) { uint32_t r; asm("cvt.rn.bf16x2.f32 %0, %1, %2;" : "=r"(r) : "f"(hi), "f"(lo)); return r; }
__device__ __forceinline__ uint32_t hfma2_bf16(uint32_t a, uint32_t b, uint32_t c) { uint32_t r; asm("fma.rn.bf16x2 %0, %1, %2, %3;" : "=r"(r) : "r"(a), "r"(b), "r"(c)); return r; }
__device__ __forceinline__ uint32_t hmul2_bf16(uint32_t a, uint32_t b) { uint32_t r; asm("mul.rn.bf16x2 %0, %1, %2;" : "=r"(r) : "r"(a), "r"(b)); return r; }
template <int LUT> __device__ __forceinline__ uint32_t lop3(uint32_t a, uint32_t b, uint32_t c) {
  uint32_t r; asm("lop3.b32 %0, %1, %2, %3, %4;" : "=r"(r) : "r"(a), "r"(b), "r"(c), "n"(LUT)); return r;
}
__device__ __forceinline__ float bf_lo(uint32_t v) { return __uint_as_float(v << 16); }
__device__ __forceinline__ float bf_hi(uint32_t v) { return __uint_as_float(v & 0xFFFF0000u); }

__device__ __forceinline__ void wgmma_n120_ss(float (&d)[60], uint32_t alo, uint32_t ahi, uint32_t blo, uint32_t bhi, int scaleD) {
  asm volatile("{\n.reg .pred p;\n.reg .b64 da, db;\nsetp.ne.b32 p, %64, 0;\nmov.b64 da, {%60, %61};\nmov.b64 db, {%62, %63};\n"
    "wgmma.mma_async.sync.aligned.m64n120k16.f32.bf16.bf16 "
    "{%0,%1,%2,%3,%4,%5,%6,%7,%8,%9,%10,%11,%12,%13,%14,%15,%16,%17,%18,%19,%20,%21,%22,%23,%24,%25,%26,%27,%28,%29,%30,%31,%32,%33,%34,%35,%36,%37,%38,%39,%40,%41,%42,%43,%44,%45,%46,%47,%48,%49,%50,%51,%52,%53,%54,%55,%56,%57,%58,%59}, "
    "da, db, p, 1, 1, 0, 1;\n}\n"
    :
      "+f"(d[0]), "+f"(d[1]), "+f"(d[2]), "+f"(d[3]), "+f"(d[4]), "+f"(d[5]), "+f"(d[6]), "+f"(d[7]),
      "+f"(d[8]), "+f"(d[9]), "+f"(d[10]), "+f"(d[11]), "+f"(d[12]), "+f"(d[13]), "+f"(d[14]), "+f"(d[15]),
      "+f"(d[16]), "+f"(d[17]), "+f"(d[18]), "+f"(d[19]), "+f"(d[20]), "+f"(d[21]), "+f"(d[22]), "+f"(d[23]),
      "+f"(d[24]), "+f"(d[25]), "+f"(d[26]), "+f"(d[27]), "+f"(d[28]), "+f"(d[29]), "+f"(d[30]), "+f"(d[31]),
      "+f"(d[32]), "+f"(d[33]), "+f"(d[34]), "+f"(d[35]), "+f"(d[36]), "+f"(d[37]), "+f"(d[38]), "+f"(d[39]),
      "+f"(d[40]), "+f"(d[41]), "+f"(d[42]), "+f"(d[43]), "+f"(d[44]), "+f"(d[45]), "+f"(d[46]), "+f"(d[47]),
      "+f"(d[48]), "+f"(d[49]), "+f"(d[50]), "+f"(d[51]), "+f"(d[52]), "+f"(d[53]), "+f"(d[54]), "+f"(d[55]),
      "+f"(d[56]), "+f"(d[57]), "+f"(d[58]), "+f"(d[59])
    : "r"(alo), "r"(ahi), "r"(blo), "r"(bhi), "r"(scaleD));
}
__device__ __forceinline__ void wgmma_n96_ss(float (&d)[48], uint32_t alo, uint32_t ahi, uint32_t blo, uint32_t bhi, int scaleD) {
  asm volatile("{\n.reg .pred p;\n.reg .b64 da, db;\nsetp.ne.b32 p, %52, 0;\nmov.b64 da, {%48, %49};\nmov.b64 db, {%50, %51};\n"
    "wgmma.mma_async.sync.aligned.m64n96k16.f32.bf16.bf16 "
    "{%0,%1,%2,%3,%4,%5,%6,%7,%8,%9,%10,%11,%12,%13,%14,%15,%16,%17,%18,%19,%20,%21,%22,%23,%24,%25,%26,%27,%28,%29,%30,%31,%32,%33,%34,%35,%36,%37,%38,%39,%40,%41,%42,%43,%44,%45,%46,%47}, "
    "da, db, p, 1, 1, 0, 1;\n}\n"
    :
      "+f"(d[0]), "+f"(d[1]), "+f"(d[2]), "+f"(d[3]), "+f"(d[4]), "+f"(d[5]), "+f"(d[6]), "+f"(d[7]),
      "+f"(d[8]), "+f"(d[9]), "+f"(d[10]), "+f"(d[11]), "+f"(d[12]), "+f"(d[13]), "+f"(d[14]), "+f"(d[15]),
      "+f"(d[16]), "+f"(d[17]), "+f"(d[18]), "+f"(d[19]), "+f"(d[20]), "+f"(d[21]), "+f"(d[22]), "+f"(d[23]),
      "+f"(d[24]), "+f"(d[25]), "+f"(d[26]), "+f"(d[27]), "+f"(d[28]), "+f"(d[29]), "+f"(d[30]), "+f"(d[31]),
      "+f"(d[32]), "+f"(d[33]), "+f"(d[34]), "+f"(d[35]), "+f"(d[36]), "+f"(d[37]), "+f"(d[38]), "+f"(d[39]),
      "+f"(d[40]), "+f"(d[41]), "+f"(d[42]), "+f"(d[43]), "+f"(d[44]), "+f"(d[45]), "+f"(d[46]), "+f"(d[47])
    : "r"(alo), "r"(ahi), "r"(blo), "r"(bhi), "r"(scaleD));
}
__device__ __forceinline__ void wgmma_n64_ss(float (&d)[32], uint32_t alo, uint32_t ahi, uint32_t blo, uint32_t bhi, int scaleD) {
  asm volatile("{\n.reg .pred p;\n.reg .b64 da, db;\nsetp.ne.b32 p, %36, 0;\nmov.b64 da, {%32, %33};\nmov.b64 db, {%34, %35};\n"
    "wgmma.mma_async.sync.aligned.m64n64k16.f32.bf16.bf16 "
    "{%0,%1,%2,%3,%4,%5,%6,%7,%8,%9,%10,%11,%12,%13,%14,%15,%16,%17,%18,%19,%20,%21,%22,%23,%24,%25,%26,%27,%28,%29,%30,%31}, "
    "da, db, p, 1, 1, 0, 1;\n}\n"
    :
      "+f"(d[0]), "+f"(d[1]), "+f"(d[2]), "+f"(d[3]), "+f"(d[4]), "+f"(d[5]), "+f"(d[6]), "+f"(d[7]),
      "+f"(d[8]), "+f"(d[9]), "+f"(d[10]), "+f"(d[11]), "+f"(d[12]), "+f"(d[13]), "+f"(d[14]), "+f"(d[15]),
      "+f"(d[16]), "+f"(d[17]), "+f"(d[18]), "+f"(d[19]), "+f"(d[20]), "+f"(d[21]), "+f"(d[22]), "+f"(d[23]),
      "+f"(d[24]), "+f"(d[25]), "+f"(d[26]), "+f"(d[27]), "+f"(d[28]), "+f"(d[29]), "+f"(d[30]), "+f"(d[31])
    : "r"(alo), "r"(ahi), "r"(blo), "r"(bhi), "r"(scaleD));
}
__device__ __forceinline__ void wgmma_n64_rs(float (&d)[32], uint32_t a0, uint32_t a1, uint32_t a2, uint32_t a3, uint32_t blo, uint32_t bhi, int scaleD) {
  asm volatile("{\n.reg .pred p;\n.reg .b64 db;\nsetp.ne.b32 p, %38, 0;\nmov.b64 db, {%36, %37};\n"
    "wgmma.mma_async.sync.aligned.m64n64k16.f32.bf16.bf16 "
    "{%0,%1,%2,%3,%4,%5,%6,%7,%8,%9,%10,%11,%12,%13,%14,%15,%16,%17,%18,%19,%20,%21,%22,%23,%24,%25,%26,%27,%28,%29,%30,%31}, "
    "{%32, %33, %34, %35}, db, p, 1, 1, 0;\n}\n"
    :
      "+f"(d[0]), "+f"(d[1]), "+f"(d[2]), "+f"(d[3]), "+f"(d[4]), "+f"(d[5]), "+f"(d[6]), "+f"(d[7]),
      "+f"(d[8]), "+f"(d[9]), "+f"(d[10]), "+f"(d[11]), "+f"(d[12]), "+f"(d[13]), "+f"(d[14]), "+f"(d[15]),
      "+f"(d[16]), "+f"(d[17]), "+f"(d[18]), "+f"(d[19]), "+f"(d[20]), "+f"(d[21]), "+f"(d[22]), "+f"(d[23]),
      "+f"(d[24]), "+f"(d[25]), "+f"(d[26]), "+f"(d[27]), "+f"(d[28]), "+f"(d[29]), "+f"(d[30]), "+f"(d[31])
    : "r"(a0), "r"(a1), "r"(a2), "r"(a3), "r"(blo), "r"(bhi), "r"(scaleD));
}
__device__ __forceinline__ void wgmma_n24_rs(float (&d)[12], uint32_t a0, uint32_t a1, uint32_t a2, uint32_t a3, uint32_t blo, uint32_t bhi, int scaleD) {
  asm volatile("{\n.reg .pred p;\n.reg .b64 db;\nsetp.ne.b32 p, %18, 0;\nmov.b64 db, {%16, %17};\n"
    "wgmma.mma_async.sync.aligned.m64n24k16.f32.bf16.bf16 "
    "{%0,%1,%2,%3,%4,%5,%6,%7,%8,%9,%10,%11}, "
    "{%12, %13, %14, %15}, db, p, 1, 1, 1;\n}\n"
    :
      "+f"(d[0]), "+f"(d[1]), "+f"(d[2]), "+f"(d[3]), "+f"(d[4]), "+f"(d[5]), "+f"(d[6]), "+f"(d[7]),
      "+f"(d[8]), "+f"(d[9]), "+f"(d[10]), "+f"(d[11])
    : "r"(a0), "r"(a1), "r"(a2), "r"(a3), "r"(blo), "r"(bhi), "r"(scaleD));
}


constexpr uint32_t MUFU_MASK = 0x4949;
constexpr float QSCALE = 0.22360679774997896f * 1.4426950408889634f;
constexpr float FAST_BOUND2 = 8100.f;
constexpr float FAST_VMAX = 1.0e6f;

constexpr int AB_STAGE = 49152;
constexpr int KV_TILE = 12288;
constexpr int D_STAGE = 28672;
constexpr int SM_SLAB = 196608;
constexpr int SM_PARAM = SM_SLAB + 20480;
constexpr int SM_RED = SM_PARAM + 4608;
constexpr int SM_BARS = SM_RED + 512;
constexpr int SMEM_BYTES = SM_BARS + 512;
constexpr int B_FULL = 0, B_EMPTY = 32, B_PREADY = 64, B_SLAB = 80, B_SLABFREE = 96, B_QKV = 104, B_KV = 112, B_KVFREE = 240, B_DFULL = 288, B_DEMPTY = 336;
constexpr int NB_WG = 1, NB_QKV = 6, NB_HID = 7, NB_ATT = 8, NB_HELP = 9, NB_FIN = 10;

__device__ __forceinline__ void st_tagged(float2* p, float v, float tag) {
  asm volatile("{\n.reg .b64 v;\nmov.b64 v, {%1, %2};\nst.relaxed.gpu.global.b64 [%0], v;\n}" ::"l"(p), "f"(v), "f"(tag) : "memory");
}
__device__ __forceinline__ bool ld_tagged(const float2* p, float& v, float tag) {
  float tg;
  asm volatile("{\n.reg .b64 v;\nld.relaxed.gpu.global.b64 v, [%2];\nmov.b64 {%0, %1}, v;\n}" : "=f"(v), "=f"(tg) : "l"(p) : "memory");
  return __float_as_uint(tg) == __float_as_uint(tag);
}
__device__ __forceinline__ void publish(unsigned* cnt) {
  asm volatile("red.release.gpu.global.add.u32 [%0], 1;" ::"l"(cnt) : "memory");
}
__device__ __forceinline__ void wait_counter(const unsigned* cnt, unsigned target) {
  unsigned cur; int spins = 0;
  do { asm volatile("ld.acquire.gpu.global.u32 %0, [%1];" : "=r"(cur) : "l"(cnt) : "memory"); } while ((int)(cur - target) < 0 && ++spins < (1 << 22));
  asm volatile("fence.proxy.async.global;" ::: "memory");
}

__device__ __forceinline__ uint32_t exp2_pair(float ta, float tb, uint32_t one2) {
  const uint32_t v = __byte_perm(__float_as_uint(ta), __float_as_uint(tb), 0x6521);
  const uint32_t m = lop3<0xEA>(v, 0x007F007Fu, one2);
  const uint32_t q = hfma2_bf16(m, 0xBDF4BDF4u, 0x3EB43EB4u);
  const uint32_t p = hfma2_bf16(q, m, 0xBF3BBF3Bu);
  return hmul2_bf16(v, p);
}
__device__ __forceinline__ void exp_tile(const float (&s)[32], uint32_t (&p)[16], const uint32_t mask, uint32_t one2) {
  #pragma unroll
  for (int i = 0; i < 8; i++) {
    if ((mask >> i) & 1) {
      p[2 * i] = pack_bf16(ex2(s[4 * i]), ex2(s[4 * i + 1]));
      p[2 * i + 1] = pack_bf16(ex2(s[4 * i + 2]), ex2(s[4 * i + 3]));
    } else {
      p[2 * i] = exp2_pair(s[4 * i], s[4 * i + 1], one2);
      p[2 * i + 1] = exp2_pair(s[4 * i + 2], s[4 * i + 3], one2);
    }
  }
}
__device__ __forceinline__ void issue_qk(float (&s)[32], const uint32_t (&qa)[8], uint32_t klo) {
  wgmma_n64_rs(s, qa[0], qa[1], qa[2], qa[3], klo | (8u << 16), 24u, 0);
  wgmma_n64_rs(s, qa[4], qa[5], qa[6], qa[7], klo + 16u, 24u, 1);
}
__device__ __forceinline__ void issue_pv(float (&o)[12], const uint32_t (&p)[16], uint32_t vlo) {
  #pragma unroll
  for (int kk = 0; kk < 4; kk++) wgmma_n24_rs(o, p[4 * kk], p[4 * kk + 1], p[4 * kk + 2], p[4 * kk + 3], vlo + kk * 48u, 8u, 1);
}

template <int V> struct IntC { static constexpr int value = V; };
struct Maps { CUtensorMap x, wqkv, wq4, w1, sq, s1, w2, wo; };

__global__ void __launch_bounds__(640, 1)
fused_block(const __grid_constant__ Maps tm, const __nv_bfloat16* __restrict__ x, const __nv_bfloat16* __restrict__ wqkv,
            const __nv_bfloat16* __restrict__ w1, const __nv_bfloat16* __restrict__ b1,
            const __nv_bfloat16* __restrict__ w2, const __nv_bfloat16* __restrict__ wo, const __nv_bfloat16* __restrict__ b2,
            __nv_bfloat16* __restrict__ out) {
  extern __shared__ __align__(1024) uint8_t smem[];
  const uint32_t sb = smem_u32(smem);
  const uint32_t sd = sb & 0x3FFFF;
  const uint32_t bar = sb + SM_BARS;
  float* s_cs = reinterpret_cast<float*>(smem + SM_PARAM);
  float* s_cs1 = s_cs + 240;
  float* s_b1h = s_cs1 + 192;
  float4* s_row = reinterpret_cast<float4*>(smem + SM_PARAM + 2560);
  const int tid = threadIdx.x, lane = tid & 31;
  const int warp = __shfl_sync(~0u, tid >> 5, 0), wg = warp >> 2;
  const int bid = blockIdx.x, rank = bid & 1;
  const int cbA = (bid >> 1) & 7, rbA = ((bid >> 4) << 1) | rank;
  const int hd = bid >> 2, qq = bid & 3;
  const int rbD = ((bid >> 3) << 1) | rank, cbD = (bid >> 1) & 3;

  if (tid == 0) {
    for (int s = 0; s < 4; s++) { mbar_init(bar + B_FULL + 8 * s, 1); mbar_init(bar + B_EMPTY + 8 * s, 32); }
    mbar_init(bar + B_PREADY, 64); mbar_init(bar + B_PREADY + 8, 64); mbar_init(bar + B_SLAB, 1); mbar_init(bar + B_SLAB + 8, 1);
    mbar_init(bar + B_SLABFREE, 64); mbar_init(bar + B_QKV, 1);
    for (int j = 0; j < 16; j++) mbar_init(bar + B_KV + 8 * j, 1);
    for (int s = 0; s < 6; s++) { mbar_init(bar + B_KVFREE + 8 * s, 32); mbar_init(bar + B_DFULL + 8 * s, 1); mbar_init(bar + B_DEMPTY + 8 * s, 16); }
    asm volatile("fence.mbarrier_init.release.cluster;" ::: "memory");
  }
  if (tid == 512) {
    asm volatile("prefetch.tensormap [%0];" ::"l"(&tm.x) : "memory");
    asm volatile("prefetch.tensormap [%0];" ::"l"(cbA < 7 ? &tm.wq4 : &tm.wqkv) : "memory");
    asm volatile("prefetch.tensormap [%0];" ::"l"(&tm.sq) : "memory");
  }
  __syncthreads();
  cluster_sync();

  if (wg == 4) {
    asm volatile("setmaxnreg.dec.sync.aligned.u32 32;");
    if (warp == 16) {
      if (lane == 0) {
        int s = 0; uint32_t ph = 1;
        const unsigned epoch_prev = __ldcg(&g_epoch);
        #pragma unroll 1
        for (int it = 0; it < 20; it++) {
          const int kb = it < 10 ? it : (it < 14 ? it - 4 : it - 14);
          mbar_wait(bar + B_EMPTY + 8 * s, ph);
          const uint32_t sa = sb + s * AB_STAGE, sw = sa + 16384, fb = bar + B_FULL + 8 * s;
          if (it < 10) {
            mbar_expect(fb, 16384 + 32768);
            tma_2d(sa, &tm.x, kb * 64, rbA * 128, fb);
            if (cbA < 7) tma_4d_mc(sw + rank * 16384, &tm.wq4, 0, kb * 64 + rank * 32, 0, cbA * 2, fb, 3);
            else for (int b = 0; b < 4; b++) tma_2d_mc(sw + rank * 16384 + b * 4096, &tm.wqkv, cbA * 240 + b * 64 - (b >> 1) * 8, kb * 64 + rank * 32, fb, 3);
          } else {
            mbar_expect(fb, it < 14 ? 24576 : 16384 + 24576);
            if (it >= 14) tma_2d(sa, &tm.x, kb * 64, rbA * 128, fb);
            tma_3d_mc(sw + rank * 12288, &tm.w1, 0, kb * 64 + rank * 32, cbA * 6, fb, 3);
          }
          if (it == 0) {
            asm volatile("cp.async.bulk.prefetch.L2.global [%0], %1;" ::"l"((const uint8_t*)x + (size_t)bid * (S_LEN * DM * 2 / 128)), "r"(S_LEN * DM * 2 / 128) : "memory");
            asm volatile("cp.async.bulk.prefetch.L2.global [%0], %1;" ::"l"((const uint8_t*)wqkv + (size_t)bid * (DM * NQKV * 2 / 128)), "r"(DM * NQKV * 2 / 128) : "memory");
          }
          if (it == 1 && bid < 120) {
            mbar_expect(bar + B_SLAB, 20480);
            for (int i = 0; i < 4; i++) tma_2d(sb + SM_SLAB + i * 5120, &tm.sq, bid * 16, i * 160, bar + B_SLAB);
          }
          if (it == 8 && bid < 96) {
            mbar_wait(bar + B_SLABFREE, 0);
            mbar_expect(bar + B_SLAB + 8, 20480);
            for (int i = 0; i < 4; i++) tma_2d(sb + SM_SLAB + i * 5120, &tm.s1, bid * 16, i * 160, bar + B_SLAB + 8);
          }
          if (++s == 4) { s = 0; ph ^= 1; }
        }
        const unsigned epoch = epoch_prev + 1u;
        wait_counter(&g_cnt[0], epoch * 128u);
        mbar_arrive(bar + B_QKV);
        const uint8_t* ksrc = reinterpret_cast<const uint8_t*>(g_qkv + (size_t)(NH + hd) * 256 * 192);
        const uint8_t* vsrc = reinterpret_cast<const uint8_t*>(g_qkv + (size_t)(2 * NH + hd) * 256 * 192);
        #pragma unroll 1
        for (int j = 0; j < 16; j++) {
          if ((j & 3) == 0) mbar_wait(bar + B_EMPTY + 8 * (j >> 2), ph);
          mbar_expect(bar + B_KV + 8 * j, KV_TILE);
          bulk_load(sb + j * KV_TILE, ksrc + j * 6144, 6144, bar + B_KV + 8 * j);
          bulk_load(sb + j * KV_TILE + 6144, vsrc + j * 6144, 6144, bar + B_KV + 8 * j);
        }
        asm volatile("cp.async.bulk.prefetch.L2.global [%0], %1;" ::"l"((const uint8_t*)w2 + (size_t)bid * (FF * DM * 2 / 128)), "r"(FF * DM * 2 / 128) : "memory");
        asm volatile("cp.async.bulk.prefetch.L2.global [%0], %1;" ::"l"((const uint8_t*)wo + (size_t)bid * (DM * DM * 2 / 128)), "r"(DM * DM * 2 / 128) : "memory");
        wait_counter(&g_cnt[32], epoch * 128u);
        s = 0; ph = 1;
        #pragma unroll 1
        for (int kb = 0; kb < 34; kb++) {
          if (kb == 24) {
            wait_counter(&g_cnt[64 + 32 * (rbD >> 3)], epoch * 32u);
            if (bid == 0) g_epoch = epoch;
          }
          if (kb < 6) mbar_wait(bar + B_KVFREE + 8 * s, 0); else mbar_wait(bar + B_DEMPTY + 8 * s, ph);
          const uint32_t sa = sb + s * D_STAGE, fb = bar + B_DFULL + 8 * s;
          mbar_expect(fb, D_STAGE);
          const int kk = kb < 24 ? kb : kb - 24;
          const __nv_bfloat16* asrc = (kb < 24 ? g_hid + (size_t)((rbD >> 1) * 24 + kk) * 8192 : g_att + (size_t)((rbD >> 1) * 10 + kk) * 8192) + (rbD & 1) * 4096;
          bulk_load(sa, asrc, 8192, fb);
          tma_3d_mc(sa + 8192 + rank * 10240, kb < 24 ? &tm.w2 : &tm.wo, 0, kk * 64 + rank * 32, cbD * 5, fb, 3);
          if (++s == 6) { s = 0; ph ^= 1; }
        }
      }
    } else {
      if (warp == 19) {
        bar_sync(NB_QKV, 544);
        if (lane == 0) publish(&g_cnt[0]);
        __syncwarp();
        bar_sync(NB_HID, 544);
        if (lane == 0) publish(&g_cnt[32]);
        __syncwarp();
        bar_sync(NB_ATT, 544);
        if (lane == 0) publish(&g_cnt[64 + 32 * qq]);
        __syncwarp();
      } else {
        const int w = warp - 17, t64 = tid - 544;
        const float tag = __uint_as_float(__ldcg(&g_epoch) + 1u);
        float* s_red = reinterpret_cast<float*>(smem + SM_RED);
        auto slab_sum = [&](uint32_t fullbar, float2* dst) {
          mbar_wait(fullbar, 0);
          float a[8];
          #pragma unroll
          for (int i = 0; i < 8; i++) a[i] = 0.f;
          #pragma unroll 2
          for (int i = w; i < 40; i += 2) {
            const uint4 u = *reinterpret_cast<const uint4*>(smem + SM_SLAB + i * 512 + lane * 16);
            a[0] += bf_lo(u.x); a[1] += bf_hi(u.x); a[2] += bf_lo(u.y); a[3] += bf_hi(u.y);
            a[4] += bf_lo(u.z); a[5] += bf_hi(u.z); a[6] += bf_lo(u.w); a[7] += bf_hi(u.w);
          }
          #pragma unroll
          for (int i = 0; i < 4; i++) { const bool up = lane & 2; const float snd = up ? a[i] : a[i + 4]; a[i] = (up ? a[i + 4] : a[i]) + __shfl_xor_sync(~0u, snd, 2); }
          #pragma unroll
          for (int i = 0; i < 2; i++) { const bool up = lane & 4; const float snd = up ? a[i] : a[i + 2]; a[i] = (up ? a[i + 2] : a[i]) + __shfl_xor_sync(~0u, snd, 4); }
          { const bool up = lane & 8; const float snd = up ? a[0] : a[1]; a[0] = (up ? a[1] : a[0]) + __shfl_xor_sync(~0u, snd, 8); }
          a[0] += __shfl_xor_sync(~0u, a[0], 16);
          if (lane < 16) s_red[w * 16 + (lane & 1) * 8 + ((lane >> 1) & 1) * 4 + ((lane >> 2) & 1) * 2 + (lane >> 3)] = a[0];
          bar_sync(NB_HELP, 64);
          if (t64 < 16) st_tagged(dst + t64, s_red[t64] + s_red[16 + t64], tag);
          bar_sync(NB_HELP, 64);
        };
        if (bid < 120) slab_sum(bar + B_SLAB, g_colsum + bid * 16);
        mbar_arrive(bar + B_SLABFREE);
        {
          const float2* pc = g_colsum + cbA * 240 + t64;
          const int i3 = t64 < 48 ? 192 : 0;
          float c0, c1, c2, c3; bool ok; int spins = 0;
          do { ok = ld_tagged(pc, c0, tag); ok &= ld_tagged(pc + 64, c1, tag); ok &= ld_tagged(pc + 128, c2, tag); ok &= ld_tagged(pc + i3, c3, tag); } while (!ok && ++spins < (1 << 20));
          s_cs[t64] = c0; s_cs[64 + t64] = c1; s_cs[128 + t64] = c2; if (t64 < 48) s_cs[192 + t64] = c3;
        }
        {
          const float2* pr = g_rowstat + 2 * (rbA * 128 + t64);
          float m0, v0, m1, v1; bool ok; int spins = 0;
          do { ok = ld_tagged(pr, m0, tag); ok &= ld_tagged(pr + 1, v0, tag); ok &= ld_tagged(pr + 128, m1, tag); ok &= ld_tagged(pr + 129, v1, tag); } while (!ok && ++spins < (1 << 20));
          const float ra = 1.f / sqrtf(v0 + LN_EPS), rc = 1.f / sqrtf(v1 + LN_EPS);
          s_row[t64] = make_float4(m0, ra, ra / sqrtf(v0 * ra * ra + LN_EPS), 0.f);
          s_row[64 + t64] = make_float4(m1, rc, rc / sqrtf(v1 * rc * rc + LN_EPS), 0.f);
        }
        mbar_arrive(bar + B_PREADY);
        if (bid < 96) slab_sum(bar + B_SLAB + 8, g_colsum + NQKV + bid * 16);
        {
          const float e0 = __bfloat162float(b1[cbA * 192 + t64]), e1 = __bfloat162float(b1[cbA * 192 + 64 + t64]), e2 = __bfloat162float(b1[cbA * 192 + 128 + t64]);
          const float2* pc = g_colsum + NQKV + cbA * 192 + t64;
          float c0, c1, c2; bool ok; int spins = 0;
          do { ok = ld_tagged(pc, c0, tag); ok &= ld_tagged(pc + 64, c1, tag); ok &= ld_tagged(pc + 128, c2, tag); } while (!ok && ++spins < (1 << 20));
          s_cs1[t64] = c0; s_cs1[64 + t64] = c1; s_cs1[128 + t64] = c2;
          s_b1h[t64] = 0.5f * e0; s_b1h[64 + t64] = 0.5f * e1; s_b1h[128 + t64] = 0.5f * e2;
        }
        mbar_arrive(bar + B_PREADY + 8);
      }
    }
    cluster_sync();
    return;
  }

  asm volatile("setmaxnreg.inc.sync.aligned.u32 112;");
  const int w4 = warp & 3, g = lane >> 2, t = lane & 3;
  const int mi = wg & 1, ni = wg >> 1;
  {
    const float tag = __uint_as_float(__ldcg(&g_epoch) + 1u);
    const int row = bid * 16 + warp;
    const uint2* px = reinterpret_cast<const uint2*>(x + (size_t)row * DM);
    float v[20], sum = 0.f, sq = 0.f;
    #pragma unroll
    for (int i = 0; i < 5; i++) {
      const uint2 u = __ldg(px + i * 32 + lane);
      v[4 * i] = bf_lo(u.x); v[4 * i + 1] = bf_hi(u.x); v[4 * i + 2] = bf_lo(u.y); v[4 * i + 3] = bf_hi(u.y);
      sum += (v[4 * i] + v[4 * i + 1]) + (v[4 * i + 2] + v[4 * i + 3]);
    }
    #pragma unroll
    for (int o = 16; o; o >>= 1) sum += __shfl_xor_sync(~0u, sum, o);
    const float mean = sum * (1.f / DM);
    #pragma unroll
    for (int i = 0; i < 20; i++) { const float d = v[i] - mean; sq = fmaf(d, d, sq); }
    #pragma unroll
    for (int o = 16; o; o >>= 1) sq += __shfl_xor_sync(~0u, sq, o);
    if (lane < 2) st_tagged(g_rowstat + 2 * row + lane, lane ? sq * (1.f / DM) : mean, tag);
  }
  int s = 0; uint32_t ph = 0;
  const int tg0 = rbA * 16 + mi * 8 + w4 * 2;
  {
    float acc[60];
    #pragma unroll 1
    for (int kb = 0; kb < 10; kb++) {
      mbar_wait(bar + B_FULL + 8 * s, ph);
      const uint32_t alo = ((sd + s * AB_STAGE + mi * 8192) >> 4) | (1u << 16);
      const uint32_t blo = ((sd + s * AB_STAGE + 16384 + ni * 8192) >> 4) | (256u << 16);
      wg_fence();
      #pragma unroll
      for (int k = 0; k < 4; k++) wgmma_n120_ss(acc, alo + k * 2, 64u | (1u << 30), blo + (k >> 1) * 1024 + (k & 1) * 128, 64u | (1u << 30), (kb | k) != 0);
      wg_commit();
      if (kb > 0) { wg_wait<1>(); if (lane < 2) mbar_arrive_cta(bar + B_EMPTY + 8 * ((s + 3) & 3), lane); }
      if (++s == 4) { s = 0; ph ^= 1; }
    }
    wg_wait<0>();
    if (lane < 2) mbar_arrive_cta(bar + B_EMPTY + 8 * ((s + 3) & 3), lane);
    mbar_wait(bar + B_PREADY, 0);
    const float4 st0 = s_row[mi * 64 + w4 * 16 + g], st1 = s_row[mi * 64 + w4 * 16 + g + 8];
    const float nm0 = -st0.x, nm1 = -st1.x;
    uint32_t* dbase = reinterpret_cast<uint32_t*>(g_qkv + ((size_t)(cbA * 12 + ni * 6) * 256 + tg0) * 192) + lane;
    auto kaug = [](int grp) { return ((MUFU_MASK >> grp) & 1) ? 0u : 0x3B8043C0u; };
    const uint32_t kaug0 = kaug(tg0 & 15), kaug1 = kaug((tg0 + 1) & 15);
    #pragma unroll
    for (int pi = 0; pi < 3; pi++) {
      const int P = cbA * 6 + ni * 3 + pi, sec = P >> 4;
      const float sc = sec == 0 ? QSCALE : 1.f;
      const float r0 = st0.y * sc, r1 = st1.y * sc;
      uint32_t* de = dbase + pi * 2 * 256 * 96;
      uint32_t* dod = de + 256 * 96;
      uint32_t w[5][2];
      #pragma unroll
      for (int gi = 0; gi < 5; gi++) {
        const int i = pi * 5 + gi;
        const float2 cs = *reinterpret_cast<const float2*>(s_cs + ni * 120 + 8 * i + 2 * t);
        w[gi][0] = pack_bf16(fmaf(nm0, cs.x, acc[4 * i]) * r0, fmaf(nm0, cs.y, acc[4 * i + 1]) * r0);
        w[gi][1] = pack_bf16(fmaf(nm1, cs.x, acc[4 * i + 2]) * r1, fmaf(nm1, cs.y, acc[4 * i + 3]) * r1);
      }
      const uint32_t aug0 = sec == 1 ? kaug0 : (sec == 0 ? 0x3F803F80u : 0x00003F80u);
      const uint32_t aug1 = sec == 1 ? kaug1 : (sec == 0 ? 0x3F803F80u : 0x00003F80u);
      const uint32_t ae0 = t == 2 ? aug0 : 0u, ae1 = t == 2 ? aug1 : 0u, ao0 = t == 0 ? aug0 : 0u, ao1 = t == 0 ? aug1 : 0u;
      de[0] = w[0][0];  de[96] = w[0][1];  de[32] = w[1][0];  de[96 + 32] = w[1][1];
      de[64] = t < 2 ? w[2][0] : ae0;   de[96 + 64] = t < 2 ? w[2][1] : ae1;
      dod[0] = w[3][0]; dod[96] = w[3][1]; dod[32] = w[4][0]; dod[96 + 32] = w[4][1];
      dod[64] = t >= 2 ? w[2][0] : ao0; dod[96 + 64] = t >= 2 ? w[2][1] : ao1;
      if (sec == 1) {
        uint32_t e0 = hfma2_bf16(w[1][0], w[1][0], hmul2_bf16(w[0][0], w[0][0])), e1 = hfma2_bf16(w[1][1], w[1][1], hmul2_bf16(w[0][1], w[0][1]));
        uint32_t o0 = hfma2_bf16(w[4][0], w[4][0], hmul2_bf16(w[3][0], w[3][0])), o1 = hfma2_bf16(w[4][1], w[4][1], hmul2_bf16(w[3][1], w[3][1]));
        if (t < 2) { e0 = hfma2_bf16(w[2][0], w[2][0], e0); e1 = hfma2_bf16(w[2][1], w[2][1], e1); }
        else       { o0 = hfma2_bf16(w[2][0], w[2][0], o0); o1 = hfma2_bf16(w[2][1], w[2][1], o1); }
        float fe0 = bf_lo(e0) + bf_hi(e0), fe1 = bf_lo(e1) + bf_hi(e1), fo0 = bf_lo(o0) + bf_hi(o0), fo1 = bf_lo(o1) + bf_hi(o1);
        #pragma unroll
        for (int o = 1; o < 4; o <<= 1) {
          fe0 += __shfl_xor_sync(~0u, fe0, o); fe1 += __shfl_xor_sync(~0u, fe1, o); fo0 += __shfl_xor_sync(~0u, fo0, o); fo1 += __shfl_xor_sync(~0u, fo1, o);
        }
        const unsigned me = __reduce_max_sync(~0u, max(__float_as_uint(fe0) & 0x7FFFFFFFu, __float_as_uint(fe1) & 0x7FFFFFFFu));
        const unsigned mo = __reduce_max_sync(~0u, max(__float_as_uint(fo0) & 0x7FFFFFFFu, __float_as_uint(fo1) & 0x7FFFFFFFu));
        if (lane == 0) { float* kn = g_knorm + (size_t)(2 * P - 32) * 128 + (tg0 >> 1); kn[0] = __uint_as_float(me); kn[128] = __uint_as_float(mo); }
      } else if (sec == 2) {
        unsigned m = 0;
        #pragma unroll
        for (int gi = 0; gi < 5; gi++) m = __vmaxu2(m, __vmaxu2(w[gi][0] & 0x7FFF7FFFu, w[gi][1] & 0x7FFF7FFFu));
        m = __reduce_max_sync(~0u, max(m << 16, m & 0xFFFF0000u));
        if (lane == 0) { float* vm = g_vmax + (size_t)(2 * P - 64) * 128 + (tg0 >> 1); vm[0] = __uint_as_float(m); vm[128] = __uint_as_float(m); }
      }
    }
    asm volatile("bar.arrive %0, 544;" ::"n"(NB_QKV) : "memory");
  }
  uint32_t qa[8];
  unsigned kmax_bits, vmax_bits;
  auto load_q = [&](int tg) {
    const uint32_t* qp = reinterpret_cast<const uint32_t*>(g_qkv + ((size_t)hd * 256 + tg) * 192) + lane;
    qa[0] = __ldcg(qp); qa[1] = __ldcg(qp + 96); qa[2] = __ldcg(qp + 32); qa[3] = __ldcg(qp + 96 + 32);
    qa[4] = __ldcg(qp + 64); qa[5] = __ldcg(qp + 96 + 64); qa[6] = 0; qa[7] = 0;
    asm volatile("" : "+r"(qa[6]), "+r"(qa[7]));
  };
  {
    float acc[48];
    #pragma unroll 1
    for (int kb = 0; kb < 10; kb++) {
      mbar_wait(bar + B_FULL + 8 * s, ph);
      const uint32_t alo = ((sd + s * AB_STAGE + mi * 8192) >> 4) | (1u << 16);
      const uint32_t blo = ((sd + s * AB_STAGE + 16384 + ni * 3 * 2048) >> 4) | (128u << 16);
      wg_fence();
      #pragma unroll
      for (int k = 0; k < 4; k++) wgmma_n96_ss(acc, alo + k * 2, 64u | (1u << 30), blo + (k >> 1) * 768 + (k & 1) * 64, 32u | (2u << 30), (kb | k) != 0);
      wg_commit();
      if (kb > 0) { wg_wait<1>(); if (lane < 2) mbar_arrive_cta(bar + B_EMPTY + 8 * ((s + 3) & 3), lane); }
      if (++s == 4) { s = 0; ph ^= 1; }
    }
    wg_wait<0>();
    if (lane < 2) mbar_arrive_cta(bar + B_EMPTY + 8 * ((s + 3) & 3), lane);
    mbar_wait(bar + B_QKV, 0);
    load_q(qq * 64 + wg * 16 + w4 * 2);
    const float4 kn4 = __ldcg(reinterpret_cast<const float4*>(g_knorm + hd * 128) + lane), vm4 = __ldcg(reinterpret_cast<const float4*>(g_vmax + hd * 128) + lane);
    kmax_bits = max(max(__float_as_uint(kn4.x), __float_as_uint(kn4.y)), max(__float_as_uint(kn4.z), __float_as_uint(kn4.w)));
    vmax_bits = max(max(__float_as_uint(vm4.x), __float_as_uint(vm4.y)), max(__float_as_uint(vm4.z), __float_as_uint(vm4.w)));
    mbar_wait(bar + B_PREADY + 8, 0);
    const float4 st0 = s_row[mi * 64 + w4 * 16 + g], st1 = s_row[mi * 64 + w4 * 16 + g + 8];
    const float nm0 = -st0.x, nm1 = -st1.x, a0 = 0.5f * st0.z, a1 = 0.5f * st1.z;
    uint32_t* dst = reinterpret_cast<uint32_t*>(g_hid + ((size_t)(rbA * 24 + cbA * 3) * 16 + mi * 8 + w4 * 2) * 512) + lane;
    constexpr float GA = 1.5957691216057308f, GB = 1.5957691216057308f * 0.044715f * 4.f;
    #pragma unroll
    for (int i = 0; i < 12; i++) {
      const float2 cs = *reinterpret_cast<const float2*>(s_cs1 + ni * 96 + 8 * i + 2 * t);
      const float2 bb = *reinterpret_cast<const float2*>(s_b1h + ni * 96 + 8 * i + 2 * t);
      float h[4];
      h[0] = fmaf(fmaf(nm0, cs.x, acc[4 * i]), a0, bb.x);     h[1] = fmaf(fmaf(nm0, cs.y, acc[4 * i + 1]), a0, bb.y);
      h[2] = fmaf(fmaf(nm1, cs.x, acc[4 * i + 2]), a1, bb.x); h[3] = fmaf(fmaf(nm1, cs.y, acc[4 * i + 3]), a1, bb.y);
      #pragma unroll
      for (int e = 0; e < 4; e++) {
        const float u = h[e] * fmaf(h[e] * h[e], GB, GA);
        h[e] = fmaf(h[e], tanh_fast(u), h[e]);
      }
      const int kgl = ni * 12 + i;
      uint32_t* d = dst + (kgl >> 3) * 4096 + (kgl & 7) * 32;
      d[0] = pack_bf16(h[0], h[1]);
      d[256] = pack_bf16(h[2], h[3]);
    }
    asm volatile("bar.arrive %0, 544;" ::"n"(NB_HID) : "memory");
  }
  {
    const float kmax2 = __uint_as_float(__reduce_max_sync(~0u, kmax_bits)), vmax = __uint_as_float(__reduce_max_sync(~0u, vmax_bits));
    const bool odd = hd & 1;
    const uint32_t kv0 = sd >> 4, bb = bar + B_KV;
    constexpr uint32_t TB = KV_TILE >> 4, VOFF = (6144 >> 4) + (24u << 16);
    constexpr uint32_t FREE_MASK = (1u << 2) | (1u << 4) | (1u << 6) | (1u << 9) | (1u << 11) | (1u << 13);
    uint32_t one2 = 0x3F803F80u;
    asm volatile("" : "+r"(one2));

    #pragma unroll 1
    for (int r = 0; r < 2; r++) {
      const int tg = qq * 64 + wg * 16 + r * 8 + w4 * 2;
      if (r == 1) load_q(tg);
      const bool real2 = odd ? (t >= 2) : (t < 2);
      float n0 = bf_lo(qa[0]) * bf_lo(qa[0]) + bf_hi(qa[0]) * bf_hi(qa[0]) + bf_lo(qa[2]) * bf_lo(qa[2]) + bf_hi(qa[2]) * bf_hi(qa[2]);
      float n1 = bf_lo(qa[1]) * bf_lo(qa[1]) + bf_hi(qa[1]) * bf_hi(qa[1]) + bf_lo(qa[3]) * bf_lo(qa[3]) + bf_hi(qa[3]) * bf_hi(qa[3]);
      if (real2) { n0 += bf_lo(qa[4]) * bf_lo(qa[4]) + bf_hi(qa[4]) * bf_hi(qa[4]); n1 += bf_lo(qa[5]) * bf_lo(qa[5]) + bf_hi(qa[5]) * bf_hi(qa[5]); }
      n0 += __shfl_xor_sync(~0u, n0, 1); n0 += __shfl_xor_sync(~0u, n0, 2);
      n1 += __shfl_xor_sync(~0u, n1, 1); n1 += __shfl_xor_sync(~0u, n1, 2);
      const bool ok = (n0 * kmax2 * 1.06f <= FAST_BOUND2) && (n1 * kmax2 * 1.06f <= FAST_BOUND2) && (vmax <= FAST_VMAX);
      int allok;
      asm volatile("{\n.reg .pred p, q;\nsetp.ne.b32 p, %1, 0;\nbarrier.red.and.pred q, %2, 128, p;\nselp.b32 %0, 1, 0, q;\n}" : "=r"(allok) : "r"((int)ok), "r"(NB_WG + wg) : "memory");
      allok = __shfl_sync(~0u, allok, 0);
      float o[12];
      #pragma unroll
      for (int i = 0; i < 12; i++) o[i] = 0.f;
      int freed = 0;
      if (allok) {
        float s0[32], s1[32]; uint32_t p[16];
        if (r == 0) mbar_wait(bb, 0);
        wg_fence(); issue_qk(s0, qa, kv0); wg_commit(); wg_wait<0>();
        #pragma unroll 1
        for (int j = 0; j < 16; j++) {
          const uint32_t base = kv0 + j * TB;
          wg_fence(); issue_qk(s1, qa, base + 192u); wg_commit();
          exp_tile(s0, p, MUFU_MASK & 0xFF, one2);
          wg_fence(); issue_pv(o, p, base + VOFF); wg_commit();
          if (r == 0 && j < 15) mbar_wait(bb + (j + 1) * 8, 0);
          wg_wait<0>();
          wg_fence(); issue_qk(s0, qa, j < 15 ? base + TB : base); wg_commit();
          exp_tile(s1, p, MUFU_MASK >> 8, one2);
          wg_fence(); issue_pv(o, p, base + VOFF + 4 * 48u); wg_commit();
          wg_wait<0>();
          if (r == 1 && ((FREE_MASK >> j) & 1)) { if (lane < 2) mbar_arrive_cta(bar + B_KVFREE + 8 * freed, lane); freed++; }
        }
      } else {
        if (!real2) { qa[4] = 0; qa[5] = 0; }
        float m0 = -INFINITY, m1 = -INFINITY;
        float sc[32]; uint32_t p[16];
        #pragma unroll 1
        for (int u = 0; u < 32; u++) {
          const uint32_t base = kv0 + (u >> 1) * TB;
          mbar_wait(bb + (u >> 1) * 8, 0);
          wg_fence(); issue_qk(sc, qa, base + (u & 1) * 192u); wg_commit(); wg_wait<0>();
          float x0 = m0, x1 = m1;
          #pragma unroll
          for (int i = 0; i < 8; i++) { x0 = fmaxf(x0, fmaxf(sc[4 * i], sc[4 * i + 1])); x1 = fmaxf(x1, fmaxf(sc[4 * i + 2], sc[4 * i + 3])); }
          x0 = fmaxf(x0, __shfl_xor_sync(~0u, x0, 1)); x0 = fmaxf(x0, __shfl_xor_sync(~0u, x0, 2));
          x1 = fmaxf(x1, __shfl_xor_sync(~0u, x1, 1)); x1 = fmaxf(x1, __shfl_xor_sync(~0u, x1, 2));
          const float c0 = ex2(m0 - x0), c1 = ex2(m1 - x1);
          m0 = x0; m1 = x1;
          #pragma unroll
          for (int i = 0; i < 3; i++) { o[4 * i] *= c0; o[4 * i + 1] *= c0; o[4 * i + 2] *= c1; o[4 * i + 3] *= c1; }
          #pragma unroll
          for (int i = 0; i < 8; i++) {
            p[2 * i] = pack_bf16(ex2(sc[4 * i] - m0), ex2(sc[4 * i + 1] - m0));
            p[2 * i + 1] = pack_bf16(ex2(sc[4 * i + 2] - m1), ex2(sc[4 * i + 3] - m1));
          }
          wg_fence(); issue_pv(o, p, base + VOFF + (u & 1) * 4 * 48u); wg_commit(); wg_wait<0>();
        }
        if (r == 1 && lane < 2) for (int i = 0; i < 6; i++) mbar_arrive_cta(bar + B_KVFREE + 8 * i, lane);
      }
      const int src = (lane & ~3) | (odd ? 0 : 2);
      const float i0 = 1.f / __shfl_sync(~0u, o[8], src), i1 = 1.f / __shfl_sync(~0u, o[10], src);
      const int kg0 = (20 * hd) >> 3;
      uint32_t* ob = reinterpret_cast<uint32_t*>(g_att + ((size_t)(tg >> 4) * 10 * 16 + (tg & 15)) * 512) + lane;
      auto kaddr = [&](int kg) { return ob + (kg >> 3) * 4096 + (kg & 7) * 32; };
      uint32_t* d0 = kaddr(odd ? kg0 + 1 : kg0);
      uint32_t* d1 = kaddr(odd ? kg0 + 2 : kg0 + 1);
      uint32_t* d2 = kaddr(odd ? kg0 : kg0 + 2);
      d0[0] = pack_bf16(o[0] * i0, o[1] * i0); d0[256] = pack_bf16(o[2] * i1, o[3] * i1);
      d1[0] = pack_bf16(o[4] * i0, o[5] * i0); d1[256] = pack_bf16(o[6] * i1, o[7] * i1);
      if (real2) { d2[0] = pack_bf16(o[8] * i0, o[9] * i0); d2[256] = pack_bf16(o[10] * i1, o[11] * i1); }
    }
    asm volatile("bar.arrive %0, 544;" ::"n"(NB_ATT) : "memory");
  }
  auto phase_d = [&](auto nseg_c, auto mma, auto& acc) {
    constexpr int NSEG = decltype(nseg_c)::value;
    constexpr int NIT = NSEG / 2;
    const int col0 = cbD * 160 + wg * 96, row0 = rbD * 64 + w4 * 16;
    uint4 xv[NIT];
    #pragma unroll
    for (int it = 0; it < NIT; it++) {
      const int idx = it * 32 + lane, r = idx / NSEG, c8 = idx % NSEG;
      xv[it] = __ldg(reinterpret_cast<const uint4*>(x + (size_t)(row0 + r) * DM + col0 + c8 * 8));
    }
    int sD = 0; uint32_t phD = 0;
    #pragma unroll 1
    for (int kb = 0; kb < 34; kb++) {
      mbar_wait(bar + B_DFULL + 8 * sD, phD);
      const uint32_t alo = ((sd + sD * D_STAGE) >> 4) | (8u << 16);
      const uint32_t blo = ((sd + sD * D_STAGE + 8192 + wg * 3 * 2048) >> 4) | (128u << 16);
      wg_fence();
      #pragma unroll
      for (int k = 0; k < 4; k++) mma(acc, alo + k * 16, blo + (k >> 1) * 640 + (k & 1) * 64, (kb | k) != 0);
      wg_commit();
      if (kb > 0) { wg_wait<1>(); if (lane < 2) mbar_arrive_cta(bar + B_DEMPTY + 8 * (sD == 0 ? 5 : sD - 1), lane); }
      if (++sD == 6) { sD = 0; phD ^= 1; }
    }
    wg_wait<0>();
    float* stg = reinterpret_cast<float*>(smem) + warp * (16 * 100);
    uint4 bv[NIT];
    #pragma unroll
    for (int it = 0; it < NIT; it++) bv[it] = __ldg(reinterpret_cast<const uint4*>(b2 + col0 + ((it * 32 + lane) % NSEG) * 8));
    bar_sync(NB_FIN, 256);
    #pragma unroll
    for (int i = 0; i < NSEG; i++) {
      *reinterpret_cast<float2*>(stg + g * 100 + 8 * i + 2 * t) = make_float2(acc[4 * i], acc[4 * i + 1]);
      *reinterpret_cast<float2*>(stg + (g + 8) * 100 + 8 * i + 2 * t) = make_float2(acc[4 * i + 2], acc[4 * i + 3]);
    }
    __syncwarp();
    #pragma unroll
    for (int it = 0; it < NIT; it++) {
      const int idx = it * 32 + lane, r = idx / NSEG, c8 = idx % NSEG;
      const float4 a0 = *reinterpret_cast<const float4*>(stg + r * 100 + c8 * 8), a1 = *reinterpret_cast<const float4*>(stg + r * 100 + c8 * 8 + 4);
      uint4 o;
      o.x = pack_bf16(a0.x + bf_lo(bv[it].x) + bf_lo(xv[it].x), a0.y + bf_hi(bv[it].x) + bf_hi(xv[it].x));
      o.y = pack_bf16(a0.z + bf_lo(bv[it].y) + bf_lo(xv[it].y), a0.w + bf_hi(bv[it].y) + bf_hi(xv[it].y));
      o.z = pack_bf16(a1.x + bf_lo(bv[it].z) + bf_lo(xv[it].z), a1.y + bf_hi(bv[it].z) + bf_hi(xv[it].z));
      o.w = pack_bf16(a1.z + bf_lo(bv[it].w) + bf_lo(xv[it].w), a1.w + bf_hi(bv[it].w) + bf_hi(xv[it].w));
      *reinterpret_cast<uint4*>(out + (size_t)(row0 + r) * DM + col0 + c8 * 8) = o;
    }
  };
  if (wg == 0) {
    float acc[48];
    phase_d(IntC<12>{}, [](float (&a)[48], uint32_t da, uint32_t db, int sc) { wgmma_n96_ss(a, da, 64u, db, 32u | (2u << 30), sc); }, acc);
  } else if (wg == 1) {
    float acc[32];
    phase_d(IntC<8>{}, [](float (&a)[32], uint32_t da, uint32_t db, int sc) { wgmma_n64_ss(a, da, 64u, db, 32u | (2u << 30), sc); }, acc);
  }
  cluster_sync();
}

typedef CUresult (*EncodeTiledFn)(CUtensorMap*, CUtensorMapDataType, cuuint32_t, void*, const cuuint64_t*, const cuuint64_t*, const cuuint32_t*,
                                  const cuuint32_t*, CUtensorMapInterleave, CUtensorMapSwizzle, CUtensorMapL2promotion, CUtensorMapFloatOOBfill);

CUtensorMap make_map(EncodeTiledFn fn, const void* base, int rank, const cuuint64_t* dims, const cuuint64_t* strides, const cuuint32_t* box, CUtensorMapSwizzle sw) {
  CUtensorMap m;
  const cuuint32_t es[4] = {1, 1, 1, 1};
  fn(&m, CU_TENSOR_MAP_DATA_TYPE_BFLOAT16, rank, const_cast<void*>(base), dims, strides, box, es, CU_TENSOR_MAP_INTERLEAVE_NONE, sw,
                   CU_TENSOR_MAP_L2_PROMOTION_L2_128B, CU_TENSOR_MAP_FLOAT_OOB_FILL_NONE);
  return m;
}

}

extern "C" void kernel_launch(void* const* d_in, const int* in_sizes, int n_in, void* d_out, int out_size) {
  const __nv_bfloat16* x = static_cast<const __nv_bfloat16*>(d_in[0]);
  const __nv_bfloat16* wqkv = static_cast<const __nv_bfloat16*>(d_in[1]);
  const __nv_bfloat16* wo = static_cast<const __nv_bfloat16*>(d_in[2]);
  const __nv_bfloat16* w1 = static_cast<const __nv_bfloat16*>(d_in[4]);
  const __nv_bfloat16* b1 = static_cast<const __nv_bfloat16*>(d_in[5]);
  const __nv_bfloat16* w2 = static_cast<const __nv_bfloat16*>(d_in[6]);
  const __nv_bfloat16* b2 = static_cast<const __nv_bfloat16*>(d_in[7]);
  __nv_bfloat16* out = static_cast<__nv_bfloat16*>(d_out);

  static EncodeTiledFn encode = nullptr;
  if (!encode) {
    void* fn = nullptr;
    cudaDriverEntryPointQueryResult qr;
    cudaGetDriverEntryPoint("cuTensorMapEncodeTiled", &fn, cudaEnableDefault, &qr);
    encode = reinterpret_cast<EncodeTiledFn>(fn);
    cudaFuncSetAttribute(fused_block, cudaFuncAttributeMaxDynamicSharedMemorySize, SMEM_BYTES);
  }
  Maps tm;
  { const cuuint64_t d[2] = {DM, S_LEN}, st[1] = {DM * 2}; const cuuint32_t b[2] = {64, 128}; tm.x = make_map(encode, x, 2, d, st, b, CU_TENSOR_MAP_SWIZZLE_128B); }
  { const cuuint64_t d[2] = {NQKV, DM}, st[1] = {NQKV * 2}; const cuuint32_t b[2] = {64, 32}; tm.wqkv = make_map(encode, wqkv, 2, d, st, b, CU_TENSOR_MAP_SWIZZLE_128B); }
  { const cuuint64_t d[4] = {64, DM, 2, 16}, st[3] = {NQKV * 2, 128, 240}; const cuuint32_t b[4] = {64, 32, 2, 2}; tm.wq4 = make_map(encode, wqkv, 4, d, st, b, CU_TENSOR_MAP_SWIZZLE_128B); }
  { const cuuint64_t d[3] = {32, DM, FF / 32}, st[2] = {FF * 2, 64}; const cuuint32_t b[3] = {32, 32, 6}; tm.w1 = make_map(encode, w1, 3, d, st, b, CU_TENSOR_MAP_SWIZZLE_64B); }
  { const cuuint64_t d[2] = {NQKV, DM}, st[1] = {NQKV * 2}; const cuuint32_t b[2] = {16, 160}; tm.sq = make_map(encode, wqkv, 2, d, st, b, CU_TENSOR_MAP_SWIZZLE_NONE); }
  { const cuuint64_t d[2] = {FF, DM}, st[1] = {FF * 2}; const cuuint32_t b[2] = {16, 160}; tm.s1 = make_map(encode, w1, 2, d, st, b, CU_TENSOR_MAP_SWIZZLE_NONE); }
  { const cuuint64_t d[3] = {32, FF, DM / 32}, st[2] = {DM * 2, 64}; const cuuint32_t b[3] = {32, 32, 5}; tm.w2 = make_map(encode, w2, 3, d, st, b, CU_TENSOR_MAP_SWIZZLE_64B); }
  { const cuuint64_t d[3] = {32, DM, DM / 32}, st[2] = {DM * 2, 64}; const cuuint32_t b[3] = {32, 32, 5}; tm.wo = make_map(encode, wo, 3, d, st, b, CU_TENSOR_MAP_SWIZZLE_64B); }

  cudaLaunchAttribute at[1];
  at[0].id = cudaLaunchAttributeClusterDimension; at[0].val.clusterDim.x = 2; at[0].val.clusterDim.y = 1; at[0].val.clusterDim.z = 1;
  cudaLaunchConfig_t cfg = {};
  cfg.stream = cudaStreamPerThread;
  cfg.gridDim = dim3(128); cfg.blockDim = dim3(640); cfg.dynamicSmemBytes = SMEM_BYTES; cfg.attrs = at; cfg.numAttrs = 1;
  cudaLaunchKernelEx(&cfg, fused_block, tm, x, wqkv, w1, b1, w2, wo, b2, out);
}
```

```cpp
#include <cuda_runtime.h>
#include <cuda_bf16.h>
#include <cuda.h>
#include <stdint.h>

namespace {

constexpr int S_LEN = 2048, DM = 640, NH = 32, FF = 1536, NQKV = 1920;
constexpr float LN_EPS = 1e-5f;

__device__ __align__(1024) __nv_bfloat16 g_qkv[3 * NH * 256 * 192];
__device__ __align__(1024) __nv_bfloat16 g_hid[16 * 24 * 8192];
__device__ __align__(1024) __nv_bfloat16 g_att[16 * 10 * 8192];
__device__ float2 g_rowstat[2 * S_LEN];
__device__ float2 g_colsum[NQKV + FF];
__device__ float g_knorm[NH * 128];
__device__ float g_vmax[NH * 128];
__device__ unsigned g_epoch;
__device__ unsigned g_cnt[6 * 32];


__device__ __forceinline__ uint32_t smem_u32(const void* p) { return (uint32_t)__cvta_generic_to_shared(p); }
__device__ __forceinline__ void wg_fence() { asm volatile("wgmma.fence.sync.aligned;" ::: "memory"); }
__device__ __forceinline__ void wg_commit() { asm volatile("wgmma.commit_group.sync.aligned;" ::: "memory"); }
template <int N> __device__ __forceinline__ void wg_wait() { asm volatile("wgmma.wait_group.sync.aligned %0;" ::"n"(N) : "memory"); }
__device__ __forceinline__ void mbar_init(uint32_t bar, int cnt) { asm volatile("mbarrier.init.shared::cta.b64 [%0], %1;" ::"r"(bar), "r"(cnt)); }
__device__ __forceinline__ void mbar_expect(uint32_t bar, uint32_t bytes) {
  asm volatile("mbarrier.arrive.expect_tx.shared::cta.b64 _, [%0], %1;" ::"r"(bar), "r"(bytes) : "memory");
}
__device__ __forceinline__ void mbar_arrive(uint32_t bar) { asm volatile("mbarrier.arrive.shared::cta.b64 _, [%0];" ::"r"(bar) : "memory"); }
__device__ __forceinline__ void mbar_arrive_cta(uint32_t bar, uint32_t cta) {
  asm volatile("{\n.reg .b32 r;\nmapa.shared::cluster.u32 r, %0, %1;\nmbarrier.arrive.shared::cluster.b64 _, [r];\n}" ::"r"(bar), "r"(cta) : "memory");
}
__device__ __forceinline__ void mbar_wait(uint32_t bar, uint32_t parity) {
  asm volatile("{\n.reg .pred p;\nWAIT:\nmbarrier.try_wait.parity.shared::cta.b64 p, [%0], %1;\n@p bra DONE;\nbra WAIT;\nDONE:\n}" ::"r"(bar), "r"(parity) : "memory");
}
__device__ __forceinline__ void bulk_load(uint32_t dst, const void* src, uint32_t bytes, uint32_t bar) {
  asm volatile("cp.async.bulk.shared::cluster.global.mbarrier::complete_tx::bytes [%0], [%1], %2, [%3];" ::"r"(dst), "l"(src), "r"(bytes), "r"(bar) : "memory");
}
__device__ __forceinline__ void tma_2d(uint32_t dst, const CUtensorMap* tm, int c0, int c1, uint32_t bar) {
  asm volatile("cp.async.bulk.tensor.2d.shared::cluster.global.mbarrier::complete_tx::bytes [%0], [%1, {%3, %4}], [%2];" ::"r"(dst), "l"(tm), "r"(bar), "r"(c0), "r"(c1) : "memory");
}
__device__ __forceinline__ void tma_2d_mc(uint32_t dst, const CUtensorMap* tm, int c0, int c1, uint32_t bar, uint16_t mask) {
  asm volatile("cp.async.bulk.tensor.2d.shared::cluster.global.mbarrier::complete_tx::bytes.multicast::cluster [%0], [%1, {%3, %4}], [%2], %5;" ::"r"(dst), "l"(tm), "r"(bar), "r"(c0), "r"(c1), "h"(mask) : "memory");
}
__device__ __forceinline__ void tma_3d_mc(uint32_t dst, const CUtensorMap* tm, int c0, int c1, int c2, uint32_t bar, uint16_t mask) {
  asm volatile("cp.async.bulk.tensor.3d.shared::cluster.global.mbarrier::complete_tx::bytes.multicast::cluster [%0], [%1, {%3, %4, %5}], [%2], %6;" ::"r"(dst), "l"(tm), "r"(bar), "r"(c0), "r"(c1), "r"(c2), "h"(mask) : "memory");
}
__device__ __forceinline__ void tma_4d_mc(uint32_t dst, const CUtensorMap* tm, int c0, int c1, int c2, int c3, uint32_t bar, uint16_t mask) {
  asm volatile("cp.async.bulk.tensor.4d.shared::cluster.global.mbarrier::complete_tx::bytes.multicast::cluster [%0], [%1, {%3, %4, %5, %6}], [%2], %7;" ::"r"(dst), "l"(tm), "r"(bar), "r"(c0), "r"(c1), "r"(c2), "r"(c3), "h"(mask) : "memory");
}
__device__ __forceinline__ void cluster_sync() { asm volatile("barrier.cluster.arrive.relaxed.aligned;\nbarrier.cluster.wait.aligned;" ::: "memory"); }
__device__ __forceinline__ void bar_sync(int id, int n) { asm volatile("bar.sync %0, %1;" ::"r"(id), "r"(n) : "memory"); }
__device__ __forceinline__ float ex2(float x) { float y; asm("ex2.approx.ftz.f32 %0, %1;" : "=f"(y) : "f"(x)); return y; }
__device__ __forceinline__ float tanh_fast(float x) { float y; asm("tanh.approx.f32 %0, %1;" : "=f"(y) : "f"(x)); return y; }
__device__ __forceinline__ uint32_t pack_bf16(float lo, float hi) { uint32_t r; asm("cvt.rn.bf16x2.f32 %0, %1, %2;" : "=r"(r) : "f"(hi), "f"(lo)); return r; }
__device__ __forceinline__ uint32_t hfma2_bf16(uint32_t a, uint32_t b, uint32_t c) { uint32_t r; asm("fma.rn.bf16x2 %0, %1, %2, %3;" : "=r"(r) : "r"(a), "r"(b), "r"(c)); return r; }
__device__ __forceinline__ uint32_t hmul2_bf16(uint32_t a, uint32_t b) { uint32_t r; asm("mul.rn.bf16x2 %0, %1, %2;" : "=r"(r) : "r"(a), "r"(b)); return r; }
template <int LUT> __device__ __forceinline__ uint32_t lop3(uint32_t a, uint32_t b, uint32_t c) {
  uint32_t r; asm("lop3.b32 %0, %1, %2, %3, %4;" : "=r"(r) : "r"(a), "r"(b), "r"(c), "n"(LUT)); return r;
}
__device__ __forceinline__ float bf_lo(uint32_t v) { return __uint_as_float(v << 16); }
__device__ __forceinline__ float bf_hi(uint32_t v) { return __uint_as_float(v & 0xFFFF0000u); }

__device__ __forceinline__ void wgmma_n120_ss(float (&d)[60], uint32_t alo, uint32_t ahi, uint32_t blo, uint32_t bhi, int scaleD) {
  asm volatile("{\n.reg .pred p;\n.reg .b64 da, db;\nsetp.ne.b32 p, %64, 0;\nmov.b64 da, {%60, %61};\nmov.b64 db, {%62, %63};\n"
    "wgmma.mma_async.sync.aligned.m64n120k16.f32.bf16.bf16 "
    "{%0,%1,%2,%3,%4,%5,%6,%7,%8,%9,%10,%11,%12,%13,%14,%15,%16,%17,%18,%19,%20,%21,%22,%23,%24,%25,%26,%27,%28,%29,%30,%31,%32,%33,%34,%35,%36,%37,%38,%39,%40,%41,%42,%43,%44,%45,%46,%47,%48,%49,%50,%51,%52,%53,%54,%55,%56,%57,%58,%59}, "
    "da, db, p, 1, 1, 0, 1;\n}\n"
    :
      "+f"(d[0]), "+f"(d[1]), "+f"(d[2]), "+f"(d[3]), "+f"(d[4]), "+f"(d[5]), "+f"(d[6]), "+f"(d[7]),
      "+f"(d[8]), "+f"(d[9]), "+f"(d[10]), "+f"(d[11]), "+f"(d[12]), "+f"(d[13]), "+f"(d[14]), "+f"(d[15]),
      "+f"(d[16]), "+f"(d[17]), "+f"(d[18]), "+f"(d[19]), "+f"(d[20]), "+f"(d[21]), "+f"(d[22]), "+f"(d[23]),
      "+f"(d[24]), "+f"(d[25]), "+f"(d[26]), "+f"(d[27]), "+f"(d[28]), "+f"(d[29]), "+f"(d[30]), "+f"(d[31]),
      "+f"(d[32]), "+f"(d[33]), "+f"(d[34]), "+f"(d[35]), "+f"(d[36]), "+f"(d[37]), "+f"(d[38]), "+f"(d[39]),
      "+f"(d[40]), "+f"(d[41]), "+f"(d[42]), "+f"(d[43]), "+f"(d[44]), "+f"(d[45]), "+f"(d[46]), "+f"(d[47]),
      "+f"(d[48]), "+f"(d[49]), "+f"(d[50]), "+f"(d[51]), "+f"(d[52]), "+f"(d[53]), "+f"(d[54]), "+f"(d[55]),
      "+f"(d[56]), "+f"(d[57]), "+f"(d[58]), "+f"(d[59])
    : "r"(alo), "r"(ahi), "r"(blo), "r"(bhi), "r"(scaleD));
}
__device__ __forceinline__ void wgmma_n96_ss(float (&d)[48], uint32_t alo, uint32_t ahi, uint32_t blo, uint32_t bhi, int scaleD) {
  asm volatile("{\n.reg .pred p;\n.reg .b64 da, db;\nsetp.ne.b32 p, %52, 0;\nmov.b64 da, {%48, %49};\nmov.b64 db, {%50, %51};\n"
    "wgmma.mma_async.sync.aligned.m64n96k16.f32.bf16.bf16 "
    "{%0,%1,%2,%3,%4,%5,%6,%7,%8,%9,%10,%11,%12,%13,%14,%15,%16,%17,%18,%19,%20,%21,%22,%23,%24,%25,%26,%27,%28,%29,%30,%31,%32,%33,%34,%35,%36,%37,%38,%39,%40,%41,%42,%43,%44,%45,%46,%47}, "
    "da, db, p, 1, 1, 0, 1;\n}\n"
    :
      "+f"(d[0]), "+f"(d[1]), "+f"(d[2]), "+f"(d[3]), "+f"(d[4]), "+f"(d[5]), "+f"(d[6]), "+f"(d[7]),
      "+f"(d[8]), "+f"(d[9]), "+f"(d[10]), "+f"(d[11]), "+f"(d[12]), "+f"(d[13]), "+f"(d[14]), "+f"(d[15]),
      "+f"(d[16]), "+f"(d[17]), "+f"(d[18]), "+f"(d[19]), "+f"(d[20]), "+f"(d[21]), "+f"(d[22]), "+f"(d[23]),
      "+f"(d[24]), "+f"(d[25]), "+f"(d[26]), "+f"(d[27]), "+f"(d[28]), "+f"(d[29]), "+f"(d[30]), "+f"(d[31]),
      "+f"(d[32]), "+f"(d[33]), "+f"(d[34]), "+f"(d[35]), "+f"(d[36]), "+f"(d[37]), "+f"(d[38]), "+f"(d[39]),
      "+f"(d[40]), "+f"(d[41]), "+f"(d[42]), "+f"(d[43]), "+f"(d[44]), "+f"(d[45]), "+f"(d[46]), "+f"(d[47])
    : "r"(alo), "r"(ahi), "r"(blo), "r"(bhi), "r"(scaleD));
}
__device__ __forceinline__ void wgmma_n64_ss(float (&d)[32], uint32_t alo, uint32_t ahi, uint32_t blo, uint32_t bhi, int scaleD) {
  asm volatile("{\n.reg .pred p;\n.reg .b64 da, db;\nsetp.ne.b32 p, %36, 0;\nmov.b64 da, {%32, %33};\nmov.b64 db, {%34, %35};\n"
    "wgmma.mma_async.sync.aligned.m64n64k16.f32.bf16.bf16 "
    "{%0,%1,%2,%3,%4,%5,%6,%7,%8,%9,%10,%11,%12,%13,%14,%15,%16,%17,%18,%19,%20,%21,%22,%23,%24,%25,%26,%27,%28,%29,%30,%31}, "
    "da, db, p, 1, 1, 0, 1;\n}\n"
    :
      "+f"(d[0]), "+f"(d[1]), "+f"(d[2]), "+f"(d[3]), "+f"(d[4]), "+f"(d[5]), "+f"(d[6]), "+f"(d[7]),
      "+f"(d[8]), "+f"(d[9]), "+f"(d[10]), "+f"(d[11]), "+f"(d[12]), "+f"(d[13]), "+f"(d[14]), "+f"(d[15]),
      "+f"(d[16]), "+f"(d[17]), "+f"(d[18]), "+f"(d[19]), "+f"(d[20]), "+f"(d[21]), "+f"(d[22]), "+f"(d[23]),
      "+f"(d[24]), "+f"(d[25]), "+f"(d[26]), "+f"(d[27]), "+f"(d[28]), "+f"(d[29]), "+f"(d[30]), "+f"(d[31])
    : "r"(alo), "r"(ahi), "r"(blo), "r"(bhi), "r"(scaleD));
}
__device__ __forceinline__ void wgmma_n64_rs(float (&d)[32], uint32_t a0, uint32_t a1, uint32_t a2, uint32_t a3, uint32_t blo, uint32_t bhi, int scaleD) {
  asm volatile("{\n.reg .pred p;\n.reg .b64 db;\nsetp.ne.b32 p, %38, 0;\nmov.b64 db, {%36, %37};\n"
    "wgmma.mma_async.sync.aligned.m64n64k16.f32.bf16.bf16 "
    "{%0,%1,%2,%3,%4,%5,%6,%7,%8,%9,%10,%11,%12,%13,%14,%15,%16,%17,%18,%19,%20,%21,%22,%23,%24,%25,%26,%27,%28,%29,%30,%31}, "
    "{%32, %33, %34, %35}, db, p, 1, 1, 0;\n}\n"
    :
      "+f"(d[0]), "+f"(d[1]), "+f"(d[2]), "+f"(d[3]), "+f"(d[4]), "+f"(d[5]), "+f"(d[6]), "+f"(d[7]),
      "+f"(d[8]), "+f"(d[9]), "+f"(d[10]), "+f"(d[11]), "+f"(d[12]), "+f"(d[13]), "+f"(d[14]), "+f"(d[15]),
      "+f"(d[16]), "+f"(d[17]), "+f"(d[18]), "+f"(d[19]), "+f"(d[20]), "+f"(d[21]), "+f"(d[22]), "+f"(d[23]),
      "+f"(d[24]), "+f"(d[25]), "+f"(d[26]), "+f"(d[27]), "+f"(d[28]), "+f"(d[29]), "+f"(d[30]), "+f"(d[31])
    : "r"(a0), "r"(a1), "r"(a2), "r"(a3), "r"(blo), "r"(bhi), "r"(scaleD));
}
__device__ __forceinline__ void wgmma_n24_rs(float (&d)[12], uint32_t a0, uint32_t a1, uint32_t a2, uint32_t a3, uint32_t blo, uint32_t bhi, int scaleD) {
  asm volatile("{\n.reg .pred p;\n.reg .b64 db;\nsetp.ne.b32 p, %18, 0;\nmov.b64 db, {%16, %17};\n"
    "wgmma.mma_async.sync.aligned.m64n24k16.f32.bf16.bf16 "
    "{%0,%1,%2,%3,%4,%5,%6,%7,%8,%9,%10,%11}, "
    "{%12, %13, %14, %15}, db, p, 1, 1, 1;\n}\n"
    :
      "+f"(d[0]), "+f"(d[1]), "+f"(d[2]), "+f"(d[3]), "+f"(d[4]), "+f"(d[5]), "+f"(d[6]), "+f"(d[7]),
      "+f"(d[8]), "+f"(d[9]), "+f"(d[10]), "+f"(d[11])
    : "r"(a0), "r"(a1), "r"(a2), "r"(a3), "r"(blo), "r"(bhi), "r"(scaleD));
}


constexpr uint32_t MUFU_MASK = 0x4949;
constexpr float QSCALE = 0.22360679774997896f * 1.4426950408889634f;
constexpr float FAST_BOUND2 = 8100.f;
constexpr float FAST_VMAX = 1.0e6f;

constexpr int AB_STAGE = 49152;
constexpr int KV_TILE = 12288;
constexpr int D_STAGE = 28672;
constexpr int SM_SLAB = 196608;
constexpr int SM_PARAM = SM_SLAB + 20480;
constexpr int SM_RED = SM_PARAM + 4608;
constexpr int SM_BARS = 8 * D_STAGE;
constexpr int SMEM_BYTES = SM_BARS + 512;
constexpr int B_FULL = 0, B_EMPTY = 32, B_PREADY = 64, B_SLAB = 80, B_SLABFREE = 96, B_QKV = 104, B_KV = 112, B_KVFREE = 240, B_DFULL = 296, B_DEMPTY = 360;
constexpr int NB_WG = 1, NB_QKV = 6, NB_HID = 7, NB_ATT = 8, NB_HELP = 9, NB_FIN = 10;

__device__ __forceinline__ void st_tagged(float2* p, float v, float tag) {
  asm volatile("{\n.reg .b64 v;\nmov.b64 v, {%1, %2};\nst.relaxed.gpu.global.b64 [%0], v;\n}" ::"l"(p), "f"(v), "f"(tag) : "memory");
}
__device__ __forceinline__ bool ld_tagged(const float2* p, float& v, float tag) {
  float tg;
  asm volatile("{\n.reg .b64 v;\nld.relaxed.gpu.global.b64 v, [%2];\nmov.b64 {%0, %1}, v;\n}" : "=f"(v), "=f"(tg) : "l"(p) : "memory");
  return __float_as_uint(tg) == __float_as_uint(tag);
}
__device__ __forceinline__ void publish(unsigned* cnt) {
  asm volatile("red.release.gpu.global.add.u32 [%0], 1;" ::"l"(cnt) : "memory");
}
__device__ __forceinline__ void wait_counter(const unsigned* cnt, unsigned target) {
  unsigned cur; int spins = 0;
  do { asm volatile("ld.acquire.gpu.global.u32 %0, [%1];" : "=r"(cur) : "l"(cnt) : "memory"); } while ((int)(cur - target) < 0 && ++spins < (1 << 22));
  asm volatile("fence.proxy.async.global;" ::: "memory");
}

__device__ __forceinline__ uint32_t exp2_pair(float ta, float tb, uint32_t one2) {
  const uint32_t v = __byte_perm(__float_as_uint(ta), __float_as_uint(tb), 0x6521);
  const uint32_t m = lop3<0xEA>(v, 0x007F007Fu, one2);
  const uint32_t q = hfma2_bf16(m, 0xBDF4BDF4u, 0x3EB43EB4u);
  const uint32_t p = hfma2_bf16(q, m, 0xBF3BBF3Bu);
  return hmul2_bf16(v, p);
}
__device__ __forceinline__ void exp_tile(const float (&s)[32], uint32_t (&p)[16], const uint32_t mask, uint32_t one2) {
  #pragma unroll
  for (int i = 0; i < 8; i++) {
    if ((mask >> i) & 1) {
      p[2 * i] = pack_bf16(ex2(s[4 * i]), ex2(s[4 * i + 1]));
      p[2 * i + 1] = pack_bf16(ex2(s[4 * i + 2]), ex2(s[4 * i + 3]));
    } else {
      p[2 * i] = exp2_pair(s[4 * i], s[4 * i + 1], one2);
      p[2 * i + 1] = exp2_pair(s[4 * i + 2], s[4 * i + 3], one2);
    }
  }
}
__device__ __forceinline__ void issue_qk(float (&s)[32], const uint32_t (&qa)[8], uint32_t klo) {
  wgmma_n64_rs(s, qa[0], qa[1], qa[2], qa[3], klo | (8u << 16), 24u, 0);
  wgmma_n64_rs(s, qa[4], qa[5], qa[6], qa[7], klo + 16u, 24u, 1);
}
__device__ __forceinline__ void issue_pv(float (&o)[12], const uint32_t (&p)[16], uint32_t vlo) {
  #pragma unroll
  for (int kk = 0; kk < 4; kk++) wgmma_n24_rs(o, p[4 * kk], p[4 * kk + 1], p[4 * kk + 2], p[4 * kk + 3], vlo + kk * 48u, 8u, 1);
}

template <int V> struct IntC { static constexpr int value = V; };
struct Maps { CUtensorMap x, wqkv, wq4, w1, sq, s1, w2, wo; };

__global__ void __launch_bounds__(640, 1)
fused_block(const __grid_constant__ Maps tm, const __nv_bfloat16* __restrict__ x, const __nv_bfloat16* __restrict__ wqkv,
            const __nv_bfloat16* __restrict__ w1, const __nv_bfloat16* __restrict__ b1,
            const __nv_bfloat16* __restrict__ w2, const __nv_bfloat16* __restrict__ wo, const __nv_bfloat16* __restrict__ b2,
            __nv_bfloat16* __restrict__ out) {
  extern __shared__ __align__(1024) uint8_t smem[];
  const uint32_t sb = smem_u32(smem);
  const uint32_t sd = sb & 0x3FFFF;
  const uint32_t bar = sb + SM_BARS;
  float* s_cs = reinterpret_cast<float*>(smem + SM_PARAM);
  float* s_cs1 = s_cs + 240;
  float* s_b1h = s_cs1 + 192;
  float4* s_row = reinterpret_cast<float4*>(smem + SM_PARAM + 2560);
  const int tid = threadIdx.x, lane = tid & 31;
  const int warp = __shfl_sync(~0u, tid >> 5, 0), wg = warp >> 2;
  const int bid = blockIdx.x, rank = bid & 1;
  const int cbA = (bid >> 1) & 7, rbA = ((bid >> 4) << 1) | rank;
  const int hd = bid >> 2, qq = bid & 3;
  const int rbD = ((bid >> 3) << 1) | rank, cbD = (bid >> 1) & 3;

  if (tid == 0) {
    for (int s = 0; s < 4; s++) { mbar_init(bar + B_FULL + 8 * s, 1); mbar_init(bar + B_EMPTY + 8 * s, 32); }
    mbar_init(bar + B_PREADY, 64); mbar_init(bar + B_PREADY + 8, 64); mbar_init(bar + B_SLAB, 1); mbar_init(bar + B_SLAB + 8, 1);
    mbar_init(bar + B_SLABFREE, 64); mbar_init(bar + B_QKV, 1);
    for (int j = 0; j < 16; j++) mbar_init(bar + B_KV + 8 * j, 1);
    for (int s = 0; s < 7; s++) mbar_init(bar + B_KVFREE + 8 * s, 32);
    for (int s = 0; s < 8; s++) { mbar_init(bar + B_DFULL + 8 * s, 1); mbar_init(bar + B_DEMPTY + 8 * s, 16); }
    asm volatile("fence.mbarrier_init.release.cluster;" ::: "memory");
  }
  if (tid == 512) {
    asm volatile("prefetch.tensormap [%0];" ::"l"(&tm.x) : "memory");
    asm volatile("prefetch.tensormap [%0];" ::"l"(cbA < 7 ? &tm.wq4 : &tm.wqkv) : "memory");
    asm volatile("prefetch.tensormap [%0];" ::"l"(&tm.sq) : "memory");
  }
  __syncthreads();
  cluster_sync();

  if (wg == 4) {
    asm volatile("setmaxnreg.dec.sync.aligned.u32 32;");
    if (warp == 16) {
      if (lane == 0) {
        int s = 0; uint32_t ph = 1;
        const unsigned epoch_prev = __ldcg(&g_epoch);
        #pragma unroll 1
        for (int it = 0; it < 20; it++) {
          const int kb = it < 10 ? it : (it < 14 ? it - 4 : it - 14);
          mbar_wait(bar + B_EMPTY + 8 * s, ph);
          const uint32_t sa = sb + s * AB_STAGE, sw = sa + 16384, fb = bar + B_FULL + 8 * s;
          if (it < 10) {
            mbar_expect(fb, 16384 + 32768);
            tma_2d(sa, &tm.x, kb * 64, rbA * 128, fb);
            if (cbA < 7) tma_4d_mc(sw + rank * 16384, &tm.wq4, 0, kb * 64 + rank * 32, 0, cbA * 2, fb, 3);
            else for (int b = 0; b < 4; b++) tma_2d_mc(sw + rank * 16384 + b * 4096, &tm.wqkv, cbA * 240 + b * 64 - (b >> 1) * 8, kb * 64 + rank * 32, fb, 3);
          } else {
            mbar_expect(fb, it < 14 ? 24576 : 16384 + 24576);
            if (it >= 14) tma_2d(sa, &tm.x, kb * 64, rbA * 128, fb);
            tma_3d_mc(sw + rank * 12288, &tm.w1, 0, kb * 64 + rank * 32, cbA * 6, fb, 3);
          }
          if (it == 0) {
            asm volatile("cp.async.bulk.prefetch.L2.global [%0], %1;" ::"l"((const uint8_t*)x + (size_t)bid * (S_LEN * DM * 2 / 128)), "r"(S_LEN * DM * 2 / 128) : "memory");
            asm volatile("cp.async.bulk.prefetch.L2.global [%0], %1;" ::"l"((const uint8_t*)wqkv + (size_t)bid * (DM * NQKV * 2 / 128)), "r"(DM * NQKV * 2 / 128) : "memory");
          }
          if (it == 1 && bid < 120) {
            mbar_expect(bar + B_SLAB, 20480);
            for (int i = 0; i < 4; i++) tma_2d(sb + SM_SLAB + i * 5120, &tm.sq, bid * 16, i * 160, bar + B_SLAB);
          }
          if (it == 8 && bid < 96) {
            mbar_wait(bar + B_SLABFREE, 0);
            mbar_expect(bar + B_SLAB + 8, 20480);
            for (int i = 0; i < 4; i++) tma_2d(sb + SM_SLAB + i * 5120, &tm.s1, bid * 16, i * 160, bar + B_SLAB + 8);
          }
          if (++s == 4) { s = 0; ph ^= 1; }
        }
        const unsigned epoch = epoch_prev + 1u;
        wait_counter(&g_cnt[0], epoch * 128u);
        mbar_arrive(bar + B_QKV);
        const uint8_t* ksrc = reinterpret_cast<const uint8_t*>(g_qkv + (size_t)(NH + hd) * 256 * 192);
        const uint8_t* vsrc = reinterpret_cast<const uint8_t*>(g_qkv + (size_t)(2 * NH + hd) * 256 * 192);
        #pragma unroll 1
        for (int j = 0; j < 16; j++) {
          if ((j & 3) == 0) mbar_wait(bar + B_EMPTY + 8 * (j >> 2), ph);
          mbar_expect(bar + B_KV + 8 * j, KV_TILE);
          bulk_load(sb + j * KV_TILE, ksrc + j * 6144, 6144, bar + B_KV + 8 * j);
          bulk_load(sb + j * KV_TILE + 6144, vsrc + j * 6144, 6144, bar + B_KV + 8 * j);
        }
        asm volatile("cp.async.bulk.prefetch.L2.global [%0], %1;" ::"l"((const uint8_t*)w2 + (size_t)bid * (FF * DM * 2 / 128)), "r"(FF * DM * 2 / 128) : "memory");
        asm volatile("cp.async.bulk.prefetch.L2.global [%0], %1;" ::"l"((const uint8_t*)wo + (size_t)bid * (DM * DM * 2 / 128)), "r"(DM * DM * 2 / 128) : "memory");
        wait_counter(&g_cnt[32], epoch * 128u);
        s = 0; ph = 1;
        #pragma unroll 1
        for (int kb = 0; kb < 34; kb++) {
          if (kb == 24) {
            wait_counter(&g_cnt[64 + 32 * (rbD >> 3)], epoch * 32u);
            if (bid == 0) g_epoch = epoch;
          }
          if (kb < 7) mbar_wait(bar + B_KVFREE + 8 * s, 0); else if (kb > 7) mbar_wait(bar + B_DEMPTY + 8 * s, ph);
          const uint32_t sa = sb + s * D_STAGE, fb = bar + B_DFULL + 8 * s;
          mbar_expect(fb, D_STAGE);
          const int kk = kb < 24 ? kb : kb - 24;
          const __nv_bfloat16* asrc = (kb < 24 ? g_hid + (size_t)((rbD >> 1) * 24 + kk) * 8192 : g_att + (size_t)((rbD >> 1) * 10 + kk) * 8192) + (rbD & 1) * 4096;
          bulk_load(sa, asrc, 8192, fb);
          tma_3d_mc(sa + 8192 + rank * 10240, kb < 24 ? &tm.w2 : &tm.wo, 0, kk * 64 + rank * 32, cbD * 5, fb, 3);
          if (++s == 8) { s = 0; ph ^= 1; }
        }
      }
    } else {
      if (warp == 19) {
        bar_sync(NB_QKV, 544);
        if (lane == 0) publish(&g_cnt[0]);
        __syncwarp();
        bar_sync(NB_HID, 544);
        if (lane == 0) publish(&g_cnt[32]);
        __syncwarp();
        bar_sync(NB_ATT, 544);
        if (lane == 0) publish(&g_cnt[64 + 32 * qq]);
        __syncwarp();
      } else {
        const int w = warp - 17, t64 = tid - 544;
        const float tag = __uint_as_float(__ldcg(&g_epoch) + 1u);
        float* s_red = reinterpret_cast<float*>(smem + SM_RED);
        auto slab_sum = [&](uint32_t fullbar, float2* dst) {
          mbar_wait(fullbar, 0);
          float a[8];
          #pragma unroll
          for (int i = 0; i < 8; i++) a[i] = 0.f;
          #pragma unroll 2
          for (int i = w; i < 40; i += 2) {
            const uint4 u = *reinterpret_cast<const uint4*>(smem + SM_SLAB + i * 512 + lane * 16);
            a[0] += bf_lo(u.x); a[1] += bf_hi(u.x); a[2] += bf_lo(u.y); a[3] += bf_hi(u.y);
            a[4] += bf_lo(u.z); a[5] += bf_hi(u.z); a[6] += bf_lo(u.w); a[7] += bf_hi(u.w);
          }
          #pragma unroll
          for (int i = 0; i < 4; i++) { const bool up = lane & 2; const float snd = up ? a[i] : a[i + 4]; a[i] = (up ? a[i + 4] : a[i]) + __shfl_xor_sync(~0u, snd, 2); }
          #pragma unroll
          for (int i = 0; i < 2; i++) { const bool up = lane & 4; const float snd = up ? a[i] : a[i + 2]; a[i] = (up ? a[i + 2] : a[i]) + __shfl_xor_sync(~0u, snd, 4); }
          { const bool up = lane & 8; const float snd = up ? a[0] : a[1]; a[0] = (up ? a[1] : a[0]) + __shfl_xor_sync(~0u, snd, 8); }
          a[0] += __shfl_xor_sync(~0u, a[0], 16);
          if (lane < 16) s_red[w * 16 + (lane & 1) * 8 + ((lane >> 1) & 1) * 4 + ((lane >> 2) & 1) * 2 + (lane >> 3)] = a[0];
          bar_sync(NB_HELP, 64);
          if (t64 < 16) st_tagged(dst + t64, s_red[t64] + s_red[16 + t64], tag);
          bar_sync(NB_HELP, 64);
        };
        if (bid < 120) slab_sum(bar + B_SLAB, g_colsum + bid * 16);
        mbar_arrive(bar + B_SLABFREE);
        {
          const float2* pc = g_colsum + cbA * 240 + t64;
          const int i3 = t64 < 48 ? 192 : 0;
          float c0, c1, c2, c3; bool ok; int spins = 0;
          do { ok = ld_tagged(pc, c0, tag); ok &= ld_tagged(pc + 64, c1, tag); ok &= ld_tagged(pc + 128, c2, tag); ok &= ld_tagged(pc + i3, c3, tag); } while (!ok && ++spins < (1 << 20));
          s_cs[t64] = c0; s_cs[64 + t64] = c1; s_cs[128 + t64] = c2; if (t64 < 48) s_cs[192 + t64] = c3;
        }
        {
          const float2* pr = g_rowstat + 2 * (rbA * 128 + t64);
          float m0, v0, m1, v1; bool ok; int spins = 0;
          do { ok = ld_tagged(pr, m0, tag); ok &= ld_tagged(pr + 1, v0, tag); ok &= ld_tagged(pr + 128, m1, tag); ok &= ld_tagged(pr + 129, v1, tag); } while (!ok && ++spins < (1 << 20));
          const float ra = 1.f / sqrtf(v0 + LN_EPS), rc = 1.f / sqrtf(v1 + LN_EPS);
          s_row[t64] = make_float4(m0, ra, ra / sqrtf(v0 * ra * ra + LN_EPS), 0.f);
          s_row[64 + t64] = make_float4(m1, rc, rc / sqrtf(v1 * rc * rc + LN_EPS), 0.f);
        }
        mbar_arrive(bar + B_PREADY);
        if (bid < 96) slab_sum(bar + B_SLAB + 8, g_colsum + NQKV + bid * 16);
        {
          const float e0 = __bfloat162float(b1[cbA * 192 + t64]), e1 = __bfloat162float(b1[cbA * 192 + 64 + t64]), e2 = __bfloat162float(b1[cbA * 192 + 128 + t64]);
          const float2* pc = g_colsum + NQKV + cbA * 192 + t64;
          float c0, c1, c2; bool ok; int spins = 0;
          do { ok = ld_tagged(pc, c0, tag); ok &= ld_tagged(pc + 64, c1, tag); ok &= ld_tagged(pc + 128, c2, tag); } while (!ok && ++spins < (1 << 20));
          s_cs1[t64] = c0; s_cs1[64 + t64] = c1; s_cs1[128 + t64] = c2;
          s_b1h[t64] = 0.5f * e0; s_b1h[64 + t64] = 0.5f * e1; s_b1h[128 + t64] = 0.5f * e2;
        }
        mbar_arrive(bar + B_PREADY + 8);
      }
    }
    cluster_sync();
    return;
  }

  asm volatile("setmaxnreg.inc.sync.aligned.u32 112;");
  const int w4 = warp & 3, g = lane >> 2, t = lane & 3;
  const int mi = wg & 1, ni = wg >> 1;
  {
    const float tag = __uint_as_float(__ldcg(&g_epoch) + 1u);
    const int row = bid * 16 + warp;
    const uint2* px = reinterpret_cast<const uint2*>(x + (size_t)row * DM);
    float v[20], sum = 0.f, sq = 0.f;
    #pragma unroll
    for (int i = 0; i < 5; i++) {
      const uint2 u = __ldg(px + i * 32 + lane);
      v[4 * i] = bf_lo(u.x); v[4 * i + 1] = bf_hi(u.x); v[4 * i + 2] = bf_lo(u.y); v[4 * i + 3] = bf_hi(u.y);
      sum += (v[4 * i] + v[4 * i + 1]) + (v[4 * i + 2] + v[4 * i + 3]);
    }
    #pragma unroll
    for (int o = 16; o; o >>= 1) sum += __shfl_xor_sync(~0u, sum, o);
    const float mean = sum * (1.f / DM);
    #pragma unroll
    for (int i = 0; i < 20; i++) { const float d = v[i] - mean; sq = fmaf(d, d, sq); }
    #pragma unroll
    for (int o = 16; o; o >>= 1) sq += __shfl_xor_sync(~0u, sq, o);
    if (lane < 2) st_tagged(g_rowstat + 2 * row + lane, lane ? sq * (1.f / DM) : mean, tag);
  }
  int s = 0; uint32_t ph = 0;
  const int tg0 = rbA * 16 + mi * 8 + w4 * 2;
  {
    float acc[60];
    #pragma unroll 1
    for (int kb = 0; kb < 10; kb++) {
      mbar_wait(bar + B_FULL + 8 * s, ph);
      const uint32_t alo = ((sd + s * AB_STAGE + mi * 8192) >> 4) | (1u << 16);
      const uint32_t blo = ((sd + s * AB_STAGE + 16384 + ni * 8192) >> 4) | (256u << 16);
      wg_fence();
      #pragma unroll
      for (int k = 0; k < 4; k++) wgmma_n120_ss(acc, alo + k * 2, 64u | (1u << 30), blo + (k >> 1) * 1024 + (k & 1) * 128, 64u | (1u << 30), (kb | k) != 0);
      wg_commit();
      if (kb > 0) { wg_wait<1>(); if (lane < 2) mbar_arrive_cta(bar + B_EMPTY + 8 * ((s + 3) & 3), lane); }
      if (++s == 4) { s = 0; ph ^= 1; }
    }
    wg_wait<0>();
    if (lane < 2) mbar_arrive_cta(bar + B_EMPTY + 8 * ((s + 3) & 3), lane);
    mbar_wait(bar + B_PREADY, 0);
    const float4 st0 = s_row[mi * 64 + w4 * 16 + g], st1 = s_row[mi * 64 + w4 * 16 + g + 8];
    const float nm0 = -st0.x, nm1 = -st1.x;
    uint32_t* dbase = reinterpret_cast<uint32_t*>(g_qkv + ((size_t)(cbA * 12 + ni * 6) * 256 + tg0) * 192) + lane;
    auto kaug = [](int grp) { return ((MUFU_MASK >> grp) & 1) ? 0u : 0x3B8043C0u; };
    const uint32_t kaug0 = kaug(tg0 & 15), kaug1 = kaug((tg0 + 1) & 15);
    #pragma unroll
    for (int pi = 0; pi < 3; pi++) {
      const int P = cbA * 6 + ni * 3 + pi, sec = P >> 4;
      const float sc = sec == 0 ? QSCALE : 1.f;
      const float r0 = st0.y * sc, r1 = st1.y * sc;
      uint32_t* de = dbase + pi * 2 * 256 * 96;
      uint32_t* dod = de + 256 * 96;
      uint32_t w[5][2];
      #pragma unroll
      for (int gi = 0; gi < 5; gi++) {
        const int i = pi * 5 + gi;
        const float2 cs = *reinterpret_cast<const float2*>(s_cs + ni * 120 + 8 * i + 2 * t);
        w[gi][0] = pack_bf16(fmaf(nm0, cs.x, acc[4 * i]) * r0, fmaf(nm0, cs.y, acc[4 * i + 1]) * r0);
        w[gi][1] = pack_bf16(fmaf(nm1, cs.x, acc[4 * i + 2]) * r1, fmaf(nm1, cs.y, acc[4 * i + 3]) * r1);
      }
      const uint32_t aug0 = sec == 1 ? kaug0 : (sec == 0 ? 0x3F803F80u : 0x00003F80u);
      const uint32_t aug1 = sec == 1 ? kaug1 : (sec == 0 ? 0x3F803F80u : 0x00003F80u);
      const uint32_t ae0 = t == 2 ? aug0 : 0u, ae1 = t == 2 ? aug1 : 0u, ao0 = t == 0 ? aug0 : 0u, ao1 = t == 0 ? aug1 : 0u;
      de[0] = w[0][0];  de[96] = w[0][1];  de[32] = w[1][0];  de[96 + 32] = w[1][1];
      de[64] = t < 2 ? w[2][0] : ae0;   de[96 + 64] = t < 2 ? w[2][1] : ae1;
      dod[0] = w[3][0]; dod[96] = w[3][1]; dod[32] = w[4][0]; dod[96 + 32] = w[4][1];
      dod[64] = t >= 2 ? w[2][0] : ao0; dod[96 + 64] = t >= 2 ? w[2][1] : ao1;
      if (sec == 1) {
        uint32_t e0 = hfma2_bf16(w[1][0], w[1][0], hmul2_bf16(w[0][0], w[0][0])), e1 = hfma2_bf16(w[1][1], w[1][1], hmul2_bf16(w[0][1], w[0][1]));
        uint32_t o0 = hfma2_bf16(w[4][0], w[4][0], hmul2_bf16(w[3][0], w[3][0])), o1 = hfma2_bf16(w[4][1], w[4][1], hmul2_bf16(w[3][1], w[3][1]));
        if (t < 2) { e0 = hfma2_bf16(w[2][0], w[2][0], e0); e1 = hfma2_bf16(w[2][1], w[2][1], e1); }
        else       { o0 = hfma2_bf16(w[2][0], w[2][0], o0); o1 = hfma2_bf16(w[2][1], w[2][1], o1); }
        float fe0 = bf_lo(e0) + bf_hi(e0), fe1 = bf_lo(e1) + bf_hi(e1), fo0 = bf_lo(o0) + bf_hi(o0), fo1 = bf_lo(o1) + bf_hi(o1);
        #pragma unroll
        for (int o = 1; o < 4; o <<= 1) {
          fe0 += __shfl_xor_sync(~0u, fe0, o); fe1 += __shfl_xor_sync(~0u, fe1, o); fo0 += __shfl_xor_sync(~0u, fo0, o); fo1 += __shfl_xor_sync(~0u, fo1, o);
        }
        const unsigned me = __reduce_max_sync(~0u, max(__float_as_uint(fe0) & 0x7FFFFFFFu, __float_as_uint(fe1) & 0x7FFFFFFFu));
        const unsigned mo = __reduce_max_sync(~0u, max(__float_as_uint(fo0) & 0x7FFFFFFFu, __float_as_uint(fo1) & 0x7FFFFFFFu));
        if (lane == 0) { float* kn = g_knorm + (size_t)(2 * P - 32) * 128 + (tg0 >> 1); kn[0] = __uint_as_float(me); kn[128] = __uint_as_float(mo); }
      } else if (sec == 2) {
        unsigned m = 0;
        #pragma unroll
        for (int gi = 0; gi < 5; gi++) m = __vmaxu2(m, __vmaxu2(w[gi][0] & 0x7FFF7FFFu, w[gi][1] & 0x7FFF7FFFu));
        m = __reduce_max_sync(~0u, max(m << 16, m & 0xFFFF0000u));
        if (lane == 0) { float* vm = g_vmax + (size_t)(2 * P - 64) * 128 + (tg0 >> 1); vm[0] = __uint_as_float(m); vm[128] = __uint_as_float(m); }
      }
    }
    asm volatile("bar.arrive %0, 544;" ::"n"(NB_QKV) : "memory");
  }
  uint32_t qa[8];
  unsigned kmax_bits, vmax_bits;
  auto load_q = [&](int tg) {
    const uint32_t* qp = reinterpret_cast<const uint32_t*>(g_qkv + ((size_t)hd * 256 + tg) * 192) + lane;
    qa[0] = __ldcg(qp); qa[1] = __ldcg(qp + 96); qa[2] = __ldcg(qp + 32); qa[3] = __ldcg(qp + 96 + 32);
    qa[4] = __ldcg(qp + 64); qa[5] = __ldcg(qp + 96 + 64); qa[6] = 0; qa[7] = 0;
    asm volatile("" : "+r"(qa[6]), "+r"(qa[7]));
  };
  {
    float acc[48];
    #pragma unroll 1
    for (int kb = 0; kb < 10; kb++) {
      mbar_wait(bar + B_FULL + 8 * s, ph);
      const uint32_t alo = ((sd + s * AB_STAGE + mi * 8192) >> 4) | (1u << 16);
      const uint32_t blo = ((sd + s * AB_STAGE + 16384 + ni * 3 * 2048) >> 4) | (128u << 16);
      wg_fence();
      #pragma unroll
      for (int k = 0; k < 4; k++) wgmma_n96_ss(acc, alo + k * 2, 64u | (1u << 30), blo + (k >> 1) * 768 + (k & 1) * 64, 32u | (2u << 30), (kb | k) != 0);
      wg_commit();
      if (kb > 0) { wg_wait<1>(); if (lane < 2) mbar_arrive_cta(bar + B_EMPTY + 8 * ((s + 3) & 3), lane); }
      if (++s == 4) { s = 0; ph ^= 1; }
    }
    wg_wait<0>();
    if (lane < 2) mbar_arrive_cta(bar + B_EMPTY + 8 * ((s + 3) & 3), lane);
    mbar_wait(bar + B_QKV, 0);
    load_q(qq * 64 + wg * 16 + w4 * 2);
    const float4 kn4 = __ldcg(reinterpret_cast<const float4*>(g_knorm + hd * 128) + lane), vm4 = __ldcg(reinterpret_cast<const float4*>(g_vmax + hd * 128) + lane);
    kmax_bits = max(max(__float_as_uint(kn4.x), __float_as_uint(kn4.y)), max(__float_as_uint(kn4.z), __float_as_uint(kn4.w)));
    vmax_bits = max(max(__float_as_uint(vm4.x), __float_as_uint(vm4.y)), max(__float_as_uint(vm4.z), __float_as_uint(vm4.w)));
    mbar_wait(bar + B_PREADY + 8, 0);
    const float4 st0 = s_row[mi * 64 + w4 * 16 + g], st1 = s_row[mi * 64 + w4 * 16 + g + 8];
    const float nm0 = -st0.x, nm1 = -st1.x, a0 = 0.5f * st0.z, a1 = 0.5f * st1.z;
    uint32_t* dst = reinterpret_cast<uint32_t*>(g_hid + ((size_t)(rbA * 24 + cbA * 3) * 16 + mi * 8 + w4 * 2) * 512) + lane;
    constexpr float GA = 1.5957691216057308f, GB = 1.5957691216057308f * 0.044715f * 4.f;
    #pragma unroll
    for (int i = 0; i < 12; i++) {
      const float2 cs = *reinterpret_cast<const float2*>(s_cs1 + ni * 96 + 8 * i + 2 * t);
      const float2 bb = *reinterpret_cast<const float2*>(s_b1h + ni * 96 + 8 * i + 2 * t);
      float h[4];
      h[0] = fmaf(fmaf(nm0, cs.x, acc[4 * i]), a0, bb.x);     h[1] = fmaf(fmaf(nm0, cs.y, acc[4 * i + 1]), a0, bb.y);
      h[2] = fmaf(fmaf(nm1, cs.x, acc[4 * i + 2]), a1, bb.x); h[3] = fmaf(fmaf(nm1, cs.y, acc[4 * i + 3]), a1, bb.y);
      #pragma unroll
      for (int e = 0; e < 4; e++) {
        const float u = h[e] * fmaf(h[e] * h[e], GB, GA);
        h[e] = fmaf(h[e], tanh_fast(u), h[e]);
      }
      const int kgl = ni * 12 + i;
      uint32_t* d = dst + (kgl >> 3) * 4096 + (kgl & 7) * 32;
      d[0] = pack_bf16(h[0], h[1]);
      d[256] = pack_bf16(h[2], h[3]);
    }
    asm volatile("bar.arrive %0, 544;" ::"n"(NB_HID) : "memory");
  }
  {
    const float kmax2 = __uint_as_float(__reduce_max_sync(~0u, kmax_bits)), vmax = __uint_as_float(__reduce_max_sync(~0u, vmax_bits));
    const bool odd = hd & 1;
    const uint32_t kv0 = sd >> 4, bb = bar + B_KV;
    constexpr uint32_t TB = KV_TILE >> 4, VOFF = (6144 >> 4) + (24u << 16);
    constexpr uint32_t FREE_MASK = (1u << 2) | (1u << 4) | (1u << 6) | (1u << 9) | (1u << 11) | (1u << 13) | (1u << 15);
    uint32_t one2 = 0x3F803F80u;
    asm volatile("" : "+r"(one2));

    #pragma unroll 1
    for (int r = 0; r < 2; r++) {
      const int tg = qq * 64 + wg * 16 + r * 8 + w4 * 2;
      if (r == 1) load_q(tg);
      const bool real2 = odd ? (t >= 2) : (t < 2);
      float n0 = bf_lo(qa[0]) * bf_lo(qa[0]) + bf_hi(qa[0]) * bf_hi(qa[0]) + bf_lo(qa[2]) * bf_lo(qa[2]) + bf_hi(qa[2]) * bf_hi(qa[2]);
      float n1 = bf_lo(qa[1]) * bf_lo(qa[1]) + bf_hi(qa[1]) * bf_hi(qa[1]) + bf_lo(qa[3]) * bf_lo(qa[3]) + bf_hi(qa[3]) * bf_hi(qa[3]);
      if (real2) { n0 += bf_lo(qa[4]) * bf_lo(qa[4]) + bf_hi(qa[4]) * bf_hi(qa[4]); n1 += bf_lo(qa[5]) * bf_lo(qa[5]) + bf_hi(qa[5]) * bf_hi(qa[5]); }
      n0 += __shfl_xor_sync(~0u, n0, 1); n0 += __shfl_xor_sync(~0u, n0, 2);
      n1 += __shfl_xor_sync(~0u, n1, 1); n1 += __shfl_xor_sync(~0u, n1, 2);
      const bool ok = (n0 * kmax2 * 1.06f <= FAST_BOUND2) && (n1 * kmax2 * 1.06f <= FAST_BOUND2) && (vmax <= FAST_VMAX);
      int allok;
      asm volatile("{\n.reg .pred p, q;\nsetp.ne.b32 p, %1, 0;\nbarrier.red.and.pred q, %2, 128, p;\nselp.b32 %0, 1, 0, q;\n}" : "=r"(allok) : "r"((int)ok), "r"(NB_WG + wg) : "memory");
      allok = __shfl_sync(~0u, allok, 0);
      float o[12];
      #pragma unroll
      for (int i = 0; i < 12; i++) o[i] = 0.f;
      int freed = 0;
      if (allok) {
        float s0[32], s1[32]; uint32_t p[16];
        if (r == 0) mbar_wait(bb, 0);
        wg_fence(); issue_qk(s0, qa, kv0); wg_commit(); wg_wait<0>();
        #pragma unroll 1
        for (int j = 0; j < 16; j++) {
          const uint32_t base = kv0 + j * TB;
          wg_fence(); issue_qk(s1, qa, base + 192u); wg_commit();
          exp_tile(s0, p, MUFU_MASK & 0xFF, one2);
          wg_fence(); issue_pv(o, p, base + VOFF); wg_commit();
          if (r == 0 && j < 15) mbar_wait(bb + (j + 1) * 8, 0);
          wg_wait<0>();
          wg_fence(); issue_qk(s0, qa, j < 15 ? base + TB : base); wg_commit();
          exp_tile(s1, p, MUFU_MASK >> 8, one2);
          wg_fence(); issue_pv(o, p, base + VOFF + 4 * 48u); wg_commit();
          wg_wait<0>();
          if (r == 1 && ((FREE_MASK >> j) & 1)) { if (lane < 2) mbar_arrive_cta(bar + B_KVFREE + 8 * freed, lane); freed++; }
        }
      } else {
        if (!real2) { qa[4] = 0; qa[5] = 0; }
        float m0 = -INFINITY, m1 = -INFINITY;
        float sc[32]; uint32_t p[16];
        #pragma unroll 1
        for (int u = 0; u < 32; u++) {
          const uint32_t base = kv0 + (u >> 1) * TB;
          mbar_wait(bb + (u >> 1) * 8, 0);
          wg_fence(); issue_qk(sc, qa, base + (u & 1) * 192u); wg_commit(); wg_wait<0>();
          float x0 = m0, x1 = m1;
          #pragma unroll
          for (int i = 0; i < 8; i++) { x0 = fmaxf(x0, fmaxf(sc[4 * i], sc[4 * i + 1])); x1 = fmaxf(x1, fmaxf(sc[4 * i + 2], sc[4 * i + 3])); }
          x0 = fmaxf(x0, __shfl_xor_sync(~0u, x0, 1)); x0 = fmaxf(x0, __shfl_xor_sync(~0u, x0, 2));
          x1 = fmaxf(x1, __shfl_xor_sync(~0u, x1, 1)); x1 = fmaxf(x1, __shfl_xor_sync(~0u, x1, 2));
          const float c0 = ex2(m0 - x0), c1 = ex2(m1 - x1);
          m0 = x0; m1 = x1;
          #pragma unroll
          for (int i = 0; i < 3; i++) { o[4 * i] *= c0; o[4 * i + 1] *= c0; o[4 * i + 2] *= c1; o[4 * i + 3] *= c1; }
          #pragma unroll
          for (int i = 0; i < 8; i++) {
            p[2 * i] = pack_bf16(ex2(sc[4 * i] - m0), ex2(sc[4 * i + 1] - m0));
            p[2 * i + 1] = pack_bf16(ex2(sc[4 * i + 2] - m1), ex2(sc[4 * i + 3] - m1));
          }
          wg_fence(); issue_pv(o, p, base + VOFF + (u & 1) * 4 * 48u); wg_commit(); wg_wait<0>();
        }
        if (r == 1 && lane < 2) for (int i = 0; i < 7; i++) mbar_arrive_cta(bar + B_KVFREE + 8 * i, lane);
      }
      const int src = (lane & ~3) | (odd ? 0 : 2);
      const float i0 = 1.f / __shfl_sync(~0u, o[8], src), i1 = 1.f / __shfl_sync(~0u, o[10], src);
      const int kg0 = (20 * hd) >> 3;
      uint32_t* ob = reinterpret_cast<uint32_t*>(g_att + ((size_t)(tg >> 4) * 10 * 16 + (tg & 15)) * 512) + lane;
      auto kaddr = [&](int kg) { return ob + (kg >> 3) * 4096 + (kg & 7) * 32; };
      uint32_t* d0 = kaddr(odd ? kg0 + 1 : kg0);
      uint32_t* d1 = kaddr(odd ? kg0 + 2 : kg0 + 1);
      uint32_t* d2 = kaddr(odd ? kg0 : kg0 + 2);
      d0[0] = pack_bf16(o[0] * i0, o[1] * i0); d0[256] = pack_bf16(o[2] * i1, o[3] * i1);
      d1[0] = pack_bf16(o[4] * i0, o[5] * i0); d1[256] = pack_bf16(o[6] * i1, o[7] * i1);
      if (real2) { d2[0] = pack_bf16(o[8] * i0, o[9] * i0); d2[256] = pack_bf16(o[10] * i1, o[11] * i1); }
    }
    asm volatile("bar.arrive %0, 544;" ::"n"(NB_ATT) : "memory");
  }
  auto phase_d = [&](auto nseg_c, auto mma, auto& acc) {
    constexpr int NSEG = decltype(nseg_c)::value;
    constexpr int NIT = NSEG / 2;
    const int col0 = cbD * 160 + wg * 96, row0 = rbD * 64 + w4 * 16;
    uint4 xv[NIT];
    #pragma unroll
    for (int it = 0; it < NIT; it++) {
      const int idx = it * 32 + lane, r = idx / NSEG, c8 = idx % NSEG;
      xv[it] = __ldg(reinterpret_cast<const uint4*>(x + (size_t)(row0 + r) * DM + col0 + c8 * 8));
    }
    int sD = 0; uint32_t phD = 0;
    #pragma unroll 1
    for (int kb = 0; kb < 34; kb++) {
      mbar_wait(bar + B_DFULL + 8 * sD, phD);
      const uint32_t alo = ((sd + sD * D_STAGE) >> 4) | (8u << 16);
      const uint32_t blo = ((sd + sD * D_STAGE + 8192 + wg * 3 * 2048) >> 4) | (128u << 16);
      wg_fence();
      #pragma unroll
      for (int k = 0; k < 4; k++) mma(acc, alo + k * 16, blo + (k >> 1) * 640 + (k & 1) * 64, (kb | k) != 0);
      wg_commit();
      if (kb > 0) { wg_wait<1>(); if (lane < 2) mbar_arrive_cta(bar + B_DEMPTY + 8 * ((sD + 7) & 7), lane); }
      if (++sD == 8) { sD = 0; phD ^= 1; }
    }
    wg_wait<0>();
    float* stg = reinterpret_cast<float*>(smem) + warp * (16 * 100);
    uint4 bv[NIT];
    #pragma unroll
    for (int it = 0; it < NIT; it++) bv[it] = __ldg(reinterpret_cast<const uint4*>(b2 + col0 + ((it * 32 + lane) % NSEG) * 8));
    bar_sync(NB_FIN, 256);
    #pragma unroll
    for (int i = 0; i < NSEG; i++) {
      *reinterpret_cast<float2*>(stg + g * 100 + 8 * i + 2 * t) = make_float2(acc[4 * i], acc[4 * i + 1]);
      *reinterpret_cast<float2*>(stg + (g + 8) * 100 + 8 * i + 2 * t) = make_float2(acc[4 * i + 2], acc[4 * i + 3]);
    }
    __syncwarp();
    #pragma unroll
    for (int it = 0; it < NIT; it++) {
      const int idx = it * 32 + lane, r = idx / NSEG, c8 = idx % NSEG;
      const float4 a0 = *reinterpret_cast<const float4*>(stg + r * 100 + c8 * 8), a1 = *reinterpret_cast<const float4*>(stg + r * 100 + c8 * 8 + 4);
      uint4 o;
      o.x = pack_bf16(a0.x + bf_lo(bv[it].x) + bf_lo(xv[it].x), a0.y + bf_hi(bv[it].x) + bf_hi(xv[it].x));
      o.y = pack_bf16(a0.z + bf_lo(bv[it].y) + bf_lo(xv[it].y), a0.w + bf_hi(bv[it].y) + bf_hi(xv[it].y));
      o.z = pack_bf16(a1.x + bf_lo(bv[it].z) + bf_lo(xv[it].z), a1.y + bf_hi(bv[it].z) + bf_hi(xv[it].z));
      o.w = pack_bf16(a1.z + bf_lo(bv[it].w) + bf_lo(xv[it].w), a1.w + bf_hi(bv[it].w) + bf_hi(xv[it].w));
      *reinterpret_cast<uint4*>(out + (size_t)(row0 + r) * DM + col0 + c8 * 8) = o;
    }
  };
  if (wg == 0) {
    float acc[48];
    phase_d(IntC<12>{}, [](float (&a)[48], uint32_t da, uint32_t db, int sc) { wgmma_n96_ss(a, da, 64u, db, 32u | (2u << 30), sc); }, acc);
  } else if (wg == 1) {
    float acc[32];
    phase_d(IntC<8>{}, [](float (&a)[32], uint32_t da, uint32_t db, int sc) { wgmma_n64_ss(a, da, 64u, db, 32u | (2u << 30), sc); }, acc);
  }
  cluster_sync();
}

typedef CUresult (*EncodeTiledFn)(CUtensorMap*, CUtensorMapDataType, cuuint32_t, void*, const cuuint64_t*, const cuuint64_t*, const cuuint32_t*,
                                  const cuuint32_t*, CUtensorMapInterleave, CUtensorMapSwizzle, CUtensorMapL2promotion, CUtensorMapFloatOOBfill);

CUtensorMap make_map(EncodeTiledFn fn, const void* base, int rank, const cuuint64_t* dims, const cuuint64_t* strides, const cuuint32_t* box, CUtensorMapSwizzle sw) {
  CUtensorMap m;
  const cuuint32_t es[4] = {1, 1, 1, 1};
  fn(&m, CU_TENSOR_MAP_DATA_TYPE_BFLOAT16, rank, const_cast<void*>(base), dims, strides, box, es, CU_TENSOR_MAP_INTERLEAVE_NONE, sw,
                   CU_TENSOR_MAP_L2_PROMOTION_L2_128B, CU_TENSOR_MAP_FLOAT_OOB_FILL_NONE);
  return m;
}

}

extern "C" void kernel_launch(void* const* d_in, const int* in_sizes, int n_in, void* d_out, int out_size) {
  const __nv_bfloat16* x = static_cast<const __nv_bfloat16*>(d_in[0]);
  const __nv_bfloat16* wqkv = static_cast<const __nv_bfloat16*>(d_in[1]);
  const __nv_bfloat16* wo = static_cast<const __nv_bfloat16*>(d_in[2]);
  const __nv_bfloat16* w1 = static_cast<const __nv_bfloat16*>(d_in[4]);
  const __nv_bfloat16* b1 = static_cast<const __nv_bfloat16*>(d_in[5]);
  const __nv_bfloat16* w2 = static_cast<const __nv_bfloat16*>(d_in[6]);
  const __nv_bfloat16* b2 = static_cast<const __nv_bfloat16*>(d_in[7]);
  __nv_bfloat16* out = static_cast<__nv_bfloat16*>(d_out);

  static EncodeTiledFn encode = nullptr;
  if (!encode) {
    void* fn = nullptr;
    cudaDriverEntryPointQueryResult qr;
    cudaGetDriverEntryPoint("cuTensorMapEncodeTiled", &fn, cudaEnableDefault, &qr);
    encode = reinterpret_cast<EncodeTiledFn>(fn);
    cudaFuncSetAttribute(fused_block, cudaFuncAttributeMaxDynamicSharedMemorySize, SMEM_BYTES);
  }
  Maps tm;
  { const cuuint64_t d[2] = {DM, S_LEN}, st[1] = {DM * 2}; const cuuint32_t b[2] = {64, 128}; tm.x = make_map(encode, x, 2, d, st, b, CU_TENSOR_MAP_SWIZZLE_128B); }
  { const cuuint64_t d[2] = {NQKV, DM}, st[1] = {NQKV * 2}; const cuuint32_t b[2] = {64, 32}; tm.wqkv = make_map(encode, wqkv, 2, d, st, b, CU_TENSOR_MAP_SWIZZLE_128B); }
  { const cuuint64_t d[4] = {64, DM, 2, 16}, st[3] = {NQKV * 2, 128, 240}; const cuuint32_t b[4] = {64, 32, 2, 2}; tm.wq4 = make_map(encode, wqkv, 4, d, st, b, CU_TENSOR_MAP_SWIZZLE_128B); }
  { const cuuint64_t d[3] = {32, DM, FF / 32}, st[2] = {FF * 2, 64}; const cuuint32_t b[3] = {32, 32, 6}; tm.w1 = make_map(encode, w1, 3, d, st, b, CU_TENSOR_MAP_SWIZZLE_64B); }
  { const cuuint64_t d[2] = {NQKV, DM}, st[1] = {NQKV * 2}; const cuuint32_t b[2] = {16, 160}; tm.sq = make_map(encode, wqkv, 2, d, st, b, CU_TENSOR_MAP_SWIZZLE_NONE); }
  { const cuuint64_t d[2] = {FF, DM}, st[1] = {FF * 2}; const cuuint32_t b[2] = {16, 160}; tm.s1 = make_map(encode, w1, 2, d, st, b, CU_TENSOR_MAP_SWIZZLE_NONE); }
  { const cuuint64_t d[3] = {32, FF, DM / 32}, st[2] = {DM * 2, 64}; const cuuint32_t b[3] = {32, 32, 5}; tm.w2 = make_map(encode, w2, 3, d, st, b, CU_TENSOR_MAP_SWIZZLE_64B); }
  { const cuuint64_t d[3] = {32, DM, DM / 32}, st[2] = {DM * 2, 64}; const cuuint32_t b[3] = {32, 32, 5}; tm.wo = make_map(encode, wo, 3, d, st, b, CU_TENSOR_MAP_SWIZZLE_64B); }

  cudaLaunchAttribute at[1];
  at[0].id = cudaLaunchAttributeClusterDimension; at[0].val.clusterDim.x = 2; at[0].val.clusterDim.y = 1; at[0].val.clusterDim.z = 1;
  cudaLaunchConfig_t cfg = {};
  cfg.stream = cudaStreamPerThread;
  cfg.gridDim = dim3(128); cfg.blockDim = dim3(640); cfg.dynamicSmemBytes = SMEM_BYTES; cfg.attrs = at; cfg.numAttrs = 1;
  cudaLaunchKernelEx(&cfg, fused_block, tm, x, wqkv, w1, b1, w2, wo, b2, out);
}
```

```cpp
#include <cuda_runtime.h>
#include <cuda_bf16.h>
#include <cuda.h>
#include <stdint.h>

namespace {

constexpr int S_LEN = 2048, DM = 640, NH = 32, FF = 1536, NQKV = 1920;
constexpr float LN_EPS = 1e-5f;

__device__ __align__(1024) __nv_bfloat16 g_qkv[3 * NH * 256 * 192];
__device__ __align__(1024) __nv_bfloat16 g_hid[16 * 24 * 8192];
__device__ __align__(1024) __nv_bfloat16 g_att[16 * 10 * 8192];
__device__ float2 g_rowstat[2 * S_LEN];
__device__ float2 g_colsum[NQKV + FF];
__device__ float g_knorm[NH * 128];
__device__ float g_vmax[NH * 128];
__device__ unsigned g_epoch;
__device__ unsigned g_cnt[6 * 32];


__device__ __forceinline__ uint32_t smem_u32(const void* p) { return (uint32_t)__cvta_generic_to_shared(p); }
__device__ __forceinline__ void wg_fence() { asm volatile("wgmma.fence.sync.aligned;" ::: "memory"); }
__device__ __forceinline__ void wg_commit() { asm volatile("wgmma.commit_group.sync.aligned;" ::: "memory"); }
template <int N> __device__ __forceinline__ void wg_wait() { asm volatile("wgmma.wait_group.sync.aligned %0;" ::"n"(N) : "memory"); }
__device__ __forceinline__ void mbar_init(uint32_t bar, int cnt) { asm volatile("mbarrier.init.shared::cta.b64 [%0], %1;" ::"r"(bar), "r"(cnt)); }
__device__ __forceinline__ void mbar_expect(uint32_t bar, uint32_t bytes) {
  asm volatile("mbarrier.arrive.expect_tx.shared::cta.b64 _, [%0], %1;" ::"r"(bar), "r"(bytes) : "memory");
}
__device__ __forceinline__ void mbar_arrive(uint32_t bar) { asm volatile("mbarrier.arrive.shared::cta.b64 _, [%0];" ::"r"(bar) : "memory"); }
__device__ __forceinline__ void mbar_arrive_cta(uint32_t bar, uint32_t cta) {
  asm volatile("{\n.reg .b32 r;\nmapa.shared::cluster.u32 r, %0, %1;\nmbarrier.arrive.shared::cluster.b64 _, [r];\n}" ::"r"(bar), "r"(cta) : "memory");
}
__device__ __forceinline__ void mbar_wait(uint32_t bar, uint32_t parity) {
  asm volatile("{\n.reg .pred p;\nWAIT:\nmbarrier.try_wait.parity.shared::cta.b64 p, [%0], %1;\n@p bra DONE;\nbra WAIT;\nDONE:\n}" ::"r"(bar), "r"(parity) : "memory");
}
__device__ __forceinline__ void bulk_load(uint32_t dst, const void* src, uint32_t bytes, uint32_t bar) {
  asm volatile("cp.async.bulk.shared::cluster.global.mbarrier::complete_tx::bytes [%0], [%1], %2, [%3];" ::"r"(dst), "l"(src), "r"(bytes), "r"(bar) : "memory");
}
__device__ __forceinline__ void tma_2d(uint32_t dst, const CUtensorMap* tm, int c0, int c1, uint32_t bar) {
  asm volatile("cp.async.bulk.tensor.2d.shared::cluster.global.mbarrier::complete_tx::bytes [%0], [%1, {%3, %4}], [%2];" ::"r"(dst), "l"(tm), "r"(bar), "r"(c0), "r"(c1) : "memory");
}
__device__ __forceinline__ void tma_2d_mc(uint32_t dst, const CUtensorMap* tm, int c0, int c1, uint32_t bar, uint16_t mask) {
  asm volatile("cp.async.bulk.tensor.2d.shared::cluster.global.mbarrier::complete_tx::bytes.multicast::cluster [%0], [%1, {%3, %4}], [%2], %5;" ::"r"(dst), "l"(tm), "r"(bar), "r"(c0), "r"(c1), "h"(mask) : "memory");
}
__device__ __forceinline__ void tma_3d_mc(uint32_t dst, const CUtensorMap* tm, int c0, int c1, int c2, uint32_t bar, uint16_t mask) {
  asm volatile("cp.async.bulk.tensor.3d.shared::cluster.global.mbarrier::complete_tx::bytes.multicast::cluster [%0], [%1, {%3, %4, %5}], [%2], %6;" ::"r"(dst), "l"(tm), "r"(bar), "r"(c0), "r"(c1), "r"(c2), "h"(mask) : "memory");
}
__device__ __forceinline__ void tma_4d_mc(uint32_t dst, const CUtensorMap* tm, int c0, int c1, int c2, int c3, uint32_t bar, uint16_t mask) {
  asm volatile("cp.async.bulk.tensor.4d.shared::cluster.global.mbarrier::complete_tx::bytes.multicast::cluster [%0], [%1, {%3, %4, %5, %6}], [%2], %7;" ::"r"(dst), "l"(tm), "r"(bar), "r"(c0), "r"(c1), "r"(c2), "r"(c3), "h"(mask) : "memory");
}
__device__ __forceinline__ void cluster_sync() { asm volatile("barrier.cluster.arrive.relaxed.aligned;\nbarrier.cluster.wait.aligned;" ::: "memory"); }
__device__ __forceinline__ void bar_sync(int id, int n) { asm volatile("bar.sync %0, %1;" ::"r"(id), "r"(n) : "memory"); }
__device__ __forceinline__ float ex2(float x) { float y; asm("ex2.approx.ftz.f32 %0, %1;" : "=f"(y) : "f"(x)); return y; }
__device__ __forceinline__ float tanh_fast(float x) { float y; asm("tanh.approx.f32 %0, %1;" : "=f"(y) : "f"(x)); return y; }
__device__ __forceinline__ uint32_t pack_bf16(float lo, float hi) { uint32_t r; asm("cvt.rn.bf16x2.f32 %0, %1, %2;" : "=r"(r) : "f"(hi), "f"(lo)); return r; }
__device__ __forceinline__ uint32_t hfma2_bf16(uint32_t a, uint32_t b, uint32_t c) { uint32_t r; asm("fma.rn.bf16x2 %0, %1, %2, %3;" : "=r"(r) : "r"(a), "r"(b), "r"(c)); return r; }
__device__ __forceinline__ uint32_t hmul2_bf16(uint32_t a, uint32_t b) { uint32_t r; asm("mul.rn.bf16x2 %0, %1, %2;" : "=r"(r) : "r"(a), "r"(b)); return r; }
template <int LUT> __device__ __forceinline__ uint32_t lop3(uint32_t a, uint32_t b, uint32_t c) {
  uint32_t r; asm("lop3.b32 %0, %1, %2, %3, %4;" : "=r"(r) : "r"(a), "r"(b), "r"(c), "n"(LUT)); return r;
}
__device__ __forceinline__ float bf_lo(uint32_t v) { return __uint_as_float(v << 16); }
__device__ __forceinline__ float bf_hi(uint32_t v) { return __uint_as_float(v & 0xFFFF0000u); }

__device__ __forceinline__ void wgmma_n120_ss(float (&d)[60], uint32_t alo, uint32_t ahi, uint32_t blo, uint32_t bhi, int scaleD) {
  asm volatile("{\n.reg .pred p;\n.reg .b64 da, db;\nsetp.ne.b32 p, %64, 0;\nmov.b64 da, {%60, %61};\nmov.b64 db, {%62, %63};\n"
    "wgmma.mma_async.sync.aligned.m64n120k16.f32.bf16.bf16 "
    "{%0,%1,%2,%3,%4,%5,%6,%7,%8,%9,%10,%11,%12,%13,%14,%15,%16,%17,%18,%19,%20,%21,%22,%23,%24,%25,%26,%27,%28,%29,%30,%31,%32,%33,%34,%35,%36,%37,%38,%39,%40,%41,%42,%43,%44,%45,%46,%47,%48,%49,%50,%51,%52,%53,%54,%55,%56,%57,%58,%59}, "
    "da, db, p, 1, 1, 0, 1;\n}\n"
    :
      "+f"(d[0]), "+f"(d[1]), "+f"(d[2]), "+f"(d[3]), "+f"(d[4]), "+f"(d[5]), "+f"(d[6]), "+f"(d[7]),
      "+f"(d[8]), "+f"(d[9]), "+f"(d[10]), "+f"(d[11]), "+f"(d[12]), "+f"(d[13]), "+f"(d[14]), "+f"(d[15]),
      "+f"(d[16]), "+f"(d[17]), "+f"(d[18]), "+f"(d[19]), "+f"(d[20]), "+f"(d[21]), "+f"(d[22]), "+f"(d[23]),
      "+f"(d[24]), "+f"(d[25]), "+f"(d[26]), "+f"(d[27]), "+f"(d[28]), "+f"(d[29]), "+f"(d[30]), "+f"(d[31]),
      "+f"(d[32]), "+f"(d[33]), "+f"(d[34]), "+f"(d[35]), "+f"(d[36]), "+f"(d[37]), "+f"(d[38]), "+f"(d[39]),
      "+f"(d[40]), "+f"(d[41]), "+f"(d[42]), "+f"(d[43]), "+f"(d[44]), "+f"(d[45]), "+f"(d[46]), "+f"(d[47]),
      "+f"(d[48]), "+f"(d[49]), "+f"(d[50]), "+f"(d[51]), "+f"(d[52]), "+f"(d[53]), "+f"(d[54]), "+f"(d[55]),
      "+f"(d[56]), "+f"(d[57]), "+f"(d[58]), "+f"(d[59])
    : "r"(alo), "r"(ahi), "r"(blo), "r"(bhi), "r"(scaleD));
}
__device__ __forceinline__ void wgmma_n96_ss(float (&d)[48], uint32_t alo, uint32_t ahi, uint32_t blo, uint32_t bhi, int scaleD) {
  asm volatile("{\n.reg .pred p;\n.reg .b64 da, db;\nsetp.ne.b32 p, %52, 0;\nmov.b64 da, {%48, %49};\nmov.b64 db, {%50, %51};\n"
    "wgmma.mma_async.sync.aligned.m64n96k16.f32.bf16.bf16 "
    "{%0,%1,%2,%3,%4,%5,%6,%7,%8,%9,%10,%11,%12,%13,%14,%15,%16,%17,%18,%19,%20,%21,%22,%23,%24,%25,%26,%27,%28,%29,%30,%31,%32,%33,%34,%35,%36,%37,%38,%39,%40,%41,%42,%43,%44,%45,%46,%47}, "
    "da, db, p, 1, 1, 0, 1;\n}\n"
    :
      "+f"(d[0]), "+f"(d[1]), "+f"(d[2]), "+f"(d[3]), "+f"(d[4]), "+f"(d[5]), "+f"(d[6]), "+f"(d[7]),
      "+f"(d[8]), "+f"(d[9]), "+f"(d[10]), "+f"(d[11]), "+f"(d[12]), "+f"(d[13]), "+f"(d[14]), "+f"(d[15]),
      "+f"(d[16]), "+f"(d[17]), "+f"(d[18]), "+f"(d[19]), "+f"(d[20]), "+f"(d[21]), "+f"(d[22]), "+f"(d[23]),
      "+f"(d[24]), "+f"(d[25]), "+f"(d[26]), "+f"(d[27]), "+f"(d[28]), "+f"(d[29]), "+f"(d[30]), "+f"(d[31]),
      "+f"(d[32]), "+f"(d[33]), "+f"(d[34]), "+f"(d[35]), "+f"(d[36]), "+f"(d[37]), "+f"(d[38]), "+f"(d[39]),
      "+f"(d[40]), "+f"(d[41]), "+f"(d[42]), "+f"(d[43]), "+f"(d[44]), "+f"(d[45]), "+f"(d[46]), "+f"(d[47])
    : "r"(alo), "r"(ahi), "r"(blo), "r"(bhi), "r"(scaleD));
}
__device__ __forceinline__ void wgmma_n64_ss(float (&d)[32], uint32_t alo, uint32_t ahi, uint32_t blo, uint32_t bhi, int scaleD) {
  asm volatile("{\n.reg .pred p;\n.reg .b64 da, db;\nsetp.ne.b32 p, %36, 0;\nmov.b64 da, {%32, %33};\nmov.b64 db, {%34, %35};\n"
    "wgmma.mma_async.sync.aligned.m64n64k16.f32.bf16.bf16 "
    "{%0,%1,%2,%3,%4,%5,%6,%7,%8,%9,%10,%11,%12,%13,%14,%15,%16,%17,%18,%19,%20,%21,%22,%23,%24,%25,%26,%27,%28,%29,%30,%31}, "
    "da, db, p, 1, 1, 0, 1;\n}\n"
    :
      "+f"(d[0]), "+f"(d[1]), "+f"(d[2]), "+f"(d[3]), "+f"(d[4]), "+f"(d[5]), "+f"(d[6]), "+f"(d[7]),
      "+f"(d[8]), "+f"(d[9]), "+f"(d[10]), "+f"(d[11]), "+f"(d[12]), "+f"(d[13]), "+f"(d[14]), "+f"(d[15]),
      "+f"(d[16]), "+f"(d[17]), "+f"(d[18]), "+f"(d[19]), "+f"(d[20]), "+f"(d[21]), "+f"(d[22]), "+f"(d[23]),
      "+f"(d[24]), "+f"(d[25]), "+f"(d[26]), "+f"(d[27]), "+f"(d[28]), "+f"(d[29]), "+f"(d[30]), "+f"(d[31])
    : "r"(alo), "r"(ahi), "r"(blo), "r"(bhi), "r"(scaleD));
}
__device__ __forceinline__ void wgmma_n64_rs(float (&d)[32], uint32_t a0, uint32_t a1, uint32_t a2, uint32_t a3, uint32_t blo, uint32_t bhi, int scaleD) {
  asm volatile("{\n.reg .pred p;\n.reg .b64 db;\nsetp.ne.b32 p, %38, 0;\nmov.b64 db, {%36, %37};\n"
    "wgmma.mma_async.sync.aligned.m64n64k16.f32.bf16.bf16 "
    "{%0,%1,%2,%3,%4,%5,%6,%7,%8,%9,%10,%11,%12,%13,%14,%15,%16,%17,%18,%19,%20,%21,%22,%23,%24,%25,%26,%27,%28,%29,%30,%31}, "
    "{%32, %33, %34, %35}, db, p, 1, 1, 0;\n}\n"
    :
      "+f"(d[0]), "+f"(d[1]), "+f"(d[2]), "+f"(d[3]), "+f"(d[4]), "+f"(d[5]), "+f"(d[6]), "+f"(d[7]),
      "+f"(d[8]), "+f"(d[9]), "+f"(d[10]), "+f"(d[11]), "+f"(d[12]), "+f"(d[13]), "+f"(d[14]), "+f"(d[15]),
      "+f"(d[16]), "+f"(d[17]), "+f"(d[18]), "+f"(d[19]), "+f"(d[20]), "+f"(d[21]), "+f"(d[22]), "+f"(d[23]),
      "+f"(d[24]), "+f"(d[25]), "+f"(d[26]), "+f"(d[27]), "+f"(d[28]), "+f"(d[29]), "+f"(d[30]), "+f"(d[31])
    : "r"(a0), "r"(a1), "r"(a2), "r"(a3), "r"(blo), "r"(bhi), "r"(scaleD));
}
__device__ __forceinline__ void wgmma_n24_rs(float (&d)[12], uint32_t a0, uint32_t a1, uint32_t a2, uint32_t a3, uint32_t blo, uint32_t bhi, int scaleD) {
  asm volatile("{\n.reg .pred p;\n.reg .b64 db;\nsetp.ne.b32 p, %18, 0;\nmov.b64 db, {%16, %17};\n"
    "wgmma.mma_async.sync.aligned.m64n24k16.f32.bf16.bf16 "
    "{%0,%1,%2,%3,%4,%5,%6,%7,%8,%9,%10,%11}, "
    "{%12, %13, %14, %15}, db, p, 1, 1, 1;\n}\n"
    :
      "+f"(d[0]), "+f"(d[1]), "+f"(d[2]), "+f"(d[3]), "+f"(d[4]), "+f"(d[5]), "+f"(d[6]), "+f"(d[7]),
      "+f"(d[8]), "+f"(d[9]), "+f"(d[10]), "+f"(d[11])
    : "r"(a0), "r"(a1), "r"(a2), "r"(a3), "r"(blo), "r"(bhi), "r"(scaleD));
}


constexpr uint32_t MUFU_MASK = 0x4949;
constexpr float QSCALE = 0.22360679774997896f * 1.4426950408889634f;
constexpr float FAST_BOUND2 = 8100.f;
constexpr float FAST_VMAX = 1.0e6f;

constexpr int AB_STAGE = 49152;
constexpr int KV_TILE = 12288;
constexpr int D_STAGE = 28672;
constexpr int SM_SLAB = 196608;
constexpr int SM_PARAM = SM_SLAB + 20480;
constexpr int SM_RED = SM_PARAM + 4608;
constexpr int SM_BARS = 8 * D_STAGE;
constexpr int SMEM_BYTES = SM_BARS + 512;
constexpr int B_FULL = 0, B_EMPTY = 32, B_PREADY = 64, B_SLAB = 80, B_SLABFREE = 96, B_QKV = 104, B_KV = 112, B_KVFREE = 240, B_DFULL = 296, B_DEMPTY = 360;
constexpr int NB_WG = 1, NB_QKV = 6, NB_HID = 7, NB_ATT = 8, NB_HELP = 9, NB_FIN = 10;

__device__ __forceinline__ void st_tagged(float2* p, float v, float tag) {
  asm volatile("{\n.reg .b64 v;\nmov.b64 v, {%1, %2};\nst.relaxed.gpu.global.b64 [%0], v;\n}" ::"l"(p), "f"(v), "f"(tag) : "memory");
}
__device__ __forceinline__ bool ld_tagged(const float2* p, float& v, float tag) {
  float tg;
  asm volatile("{\n.reg .b64 v;\nld.relaxed.gpu.global.b64 v, [%2];\nmov.b64 {%0, %1}, v;\n}" : "=f"(v), "=f"(tg) : "l"(p) : "memory");
  return __float_as_uint(tg) == __float_as_uint(tag);
}
__device__ __forceinline__ void publish(unsigned* cnt) {
  asm volatile("red.release.gpu.global.add.u32 [%0], 1;" ::"l"(cnt) : "memory");
}
__device__ __forceinline__ void wait_counter(const unsigned* cnt, unsigned target) {
  unsigned cur; int spins = 0;
  do { asm volatile("ld.acquire.gpu.global.u32 %0, [%1];" : "=r"(cur) : "l"(cnt) : "memory"); } while ((int)(cur - target) < 0 && ++spins < (1 << 22));
  asm volatile("fence.proxy.async.global;" ::: "memory");
}

__device__ __forceinline__ uint32_t exp2_pair(float ta, float tb, uint32_t one2) {
  const uint32_t v = __byte_perm(__float_as_uint(ta), __float_as_uint(tb), 0x6521);
  const uint32_t m = lop3<0xEA>(v, 0x007F007Fu, one2);
  const uint32_t q = hfma2_bf16(m, 0xBDF4BDF4u, 0x3EB43EB4u);
  const uint32_t p = hfma2_bf16(q, m, 0xBF3BBF3Bu);
  return hmul2_bf16(v, p);
}
__device__ __forceinline__ void exp_tile(const float (&s)[32], uint32_t (&p)[16], const uint32_t mask, uint32_t one2) {
  #pragma unroll
  for (int i = 0; i < 8; i++) {
    if ((mask >> i) & 1) {
      p[2 * i] = pack_bf16(ex2(s[4 * i]), ex2(s[4 * i + 1]));
      p[2 * i + 1] = pack_bf16(ex2(s[4 * i + 2]), ex2(s[4 * i + 3]));
    } else {
      p[2 * i] = exp2_pair(s[4 * i], s[4 * i + 1], one2);
      p[2 * i + 1] = exp2_pair(s[4 * i + 2], s[4 * i + 3], one2);
    }
  }
}
__device__ __forceinline__ void issue_qk(float (&s)[32], const uint32_t (&qa)[8], uint32_t klo) {
  wgmma_n64_rs(s, qa[0], qa[1], qa[2], qa[3], klo | (8u << 16), 24u, 0);
  wgmma_n64_rs(s, qa[4], qa[5], qa[6], qa[7], klo + 16u, 24u, 1);
}
__device__ __forceinline__ void issue_pv(float (&o)[12], const uint32_t (&p)[16], uint32_t vlo) {
  #pragma unroll
  for (int kk = 0; kk < 4; kk++) wgmma_n24_rs(o, p[4 * kk], p[4 * kk + 1], p[4 * kk + 2], p[4 * kk + 3], vlo + kk * 48u, 8u, 1);
}

template <int V> struct IntC { static constexpr int value = V; };
struct Maps { CUtensorMap x, wqkv, wq4, w1, sq, s1, w2, wo; };

__global__ void __launch_bounds__(640, 1)
fused_block(const __grid_constant__ Maps tm, const __nv_bfloat16* __restrict__ x, const __nv_bfloat16* __restrict__ wqkv,
            const __nv_bfloat16* __restrict__ w1, const __nv_bfloat16* __restrict__ b1,
            const __nv_bfloat16* __restrict__ w2, const __nv_bfloat16* __restrict__ wo, const __nv_bfloat16* __restrict__ b2,
            __nv_bfloat16* __restrict__ out) {
  extern __shared__ __align__(1024) uint8_t smem[];
  const uint32_t sb = smem_u32(smem);
  const uint32_t sd = sb & 0x3FFFF;
  const uint32_t bar = sb + SM_BARS;
  float* s_cs = reinterpret_cast<float*>(smem + SM_PARAM);
  float* s_cs1 = s_cs + 240;
  float* s_b1h = s_cs1 + 192;
  float4* s_row = reinterpret_cast<float4*>(smem + SM_PARAM + 2560);
  const int tid = threadIdx.x, lane = tid & 31;
  const int warp = __shfl_sync(~0u, tid >> 5, 0), wg = warp >> 2;
  const int bid = blockIdx.x, rank = bid & 1;
  const int cbA = (bid >> 1) & 7, rbA = ((bid >> 4) << 1) | rank;
  const int hd = bid >> 2, qq = bid & 3;
  const int rbD = ((bid >> 3) << 1) | rank, cbD = (bid >> 1) & 3;

  if (tid == 0) {
    for (int s = 0; s < 4; s++) { mbar_init(bar + B_FULL + 8 * s, 1); mbar_init(bar + B_EMPTY + 8 * s, 32); }
    mbar_init(bar + B_PREADY, 64); mbar_init(bar + B_PREADY + 8, 64); mbar_init(bar + B_SLAB, 1); mbar_init(bar + B_SLAB + 8, 1);
    mbar_init(bar + B_SLABFREE, 64); mbar_init(bar + B_QKV, 1);
    for (int j = 0; j < 16; j++) mbar_init(bar + B_KV + 8 * j, 1);
    for (int s = 0; s < 7; s++) mbar_init(bar + B_KVFREE + 8 * s, 32);
    for (int s = 0; s < 8; s++) { mbar_init(bar + B_DFULL + 8 * s, 1); mbar_init(bar + B_DEMPTY + 8 * s, 16); }
    asm volatile("fence.mbarrier_init.release.cluster;" ::: "memory");
  }
  if (tid == 512) {
    asm volatile("prefetch.tensormap [%0];" ::"l"(&tm.x) : "memory");
    asm volatile("prefetch.tensormap [%0];" ::"l"(cbA < 7 ? &tm.wq4 : &tm.wqkv) : "memory");
    asm volatile("prefetch.tensormap [%0];" ::"l"(&tm.sq) : "memory");
  }
  __syncthreads();
  cluster_sync();

  if (wg == 4) {
    asm volatile("setmaxnreg.dec.sync.aligned.u32 32;");
    if (warp == 16) {
      if (lane == 0) {
        int s = 0; uint32_t ph = 1;
        const unsigned epoch_prev = __ldcg(&g_epoch);
        #pragma unroll 1
        for (int it = 0; it < 20; it++) {
          const int kb = it < 10 ? it : (it < 14 ? it - 4 : it - 14);
          mbar_wait(bar + B_EMPTY + 8 * s, ph);
          const uint32_t sa = sb + s * AB_STAGE, sw = sa + 16384, fb = bar + B_FULL + 8 * s;
          if (it < 10) {
            mbar_expect(fb, 16384 + 32768);
            tma_2d(sa, &tm.x, kb * 64, rbA * 128, fb);
            if (cbA < 7) tma_4d_mc(sw + rank * 16384, &tm.wq4, 0, kb * 64 + rank * 32, 0, cbA * 2, fb, 3);
            else for (int b = 0; b < 4; b++) tma_2d_mc(sw + rank * 16384 + b * 4096, &tm.wqkv, cbA * 240 + b * 64 - (b >> 1) * 8, kb * 64 + rank * 32, fb, 3);
          } else {
            mbar_expect(fb, it < 14 ? 24576 : 16384 + 24576);
            if (it >= 14) tma_2d(sa, &tm.x, kb * 64, rbA * 128, fb);
            tma_3d_mc(sw + rank * 12288, &tm.w1, 0, kb * 64 + rank * 32, cbA * 6, fb, 3);
          }
          if (it == 0) {
            asm volatile("cp.async.bulk.prefetch.L2.global [%0], %1;" ::"l"((const uint8_t*)x + (size_t)bid * (S_LEN * DM * 2 / 128)), "r"(S_LEN * DM * 2 / 128) : "memory");
            asm volatile("cp.async.bulk.prefetch.L2.global [%0], %1;" ::"l"((const uint8_t*)wqkv + (size_t)bid * (DM * NQKV * 2 / 128)), "r"(DM * NQKV * 2 / 128) : "memory");
          }
          if (it == 1 && bid < 120) {
            mbar_expect(bar + B_SLAB, 20480);
            for (int i = 0; i < 4; i++) tma_2d(sb + SM_SLAB + i * 5120, &tm.sq, bid * 16, i * 160, bar + B_SLAB);
          }
          if (it == 8 && bid < 96) {
            mbar_wait(bar + B_SLABFREE, 0);
            mbar_expect(bar + B_SLAB + 8, 20480);
            for (int i = 0; i < 4; i++) tma_2d(sb + SM_SLAB + i * 5120, &tm.s1, bid * 16, i * 160, bar + B_SLAB + 8);
          }
          if (++s == 4) { s = 0; ph ^= 1; }
        }
        const unsigned epoch = epoch_prev + 1u;
        wait_counter(&g_cnt[0], epoch * 128u);
        mbar_arrive(bar + B_QKV);
        const uint8_t* ksrc = reinterpret_cast<const uint8_t*>(g_qkv + (size_t)(NH + hd) * 256 * 192);
        const uint8_t* vsrc = reinterpret_cast<const uint8_t*>(g_qkv + (size_t)(2 * NH + hd) * 256 * 192);
        #pragma unroll 1
        for (int j = 0; j < 16; j++) {
          if ((j & 3) == 0) mbar_wait(bar + B_EMPTY + 8 * (j >> 2), ph);
          mbar_expect(bar + B_KV + 8 * j, KV_TILE);
          bulk_load(sb + j * KV_TILE, ksrc + j * 6144, 6144, bar + B_KV + 8 * j);
          bulk_load(sb + j * KV_TILE + 6144, vsrc + j * 6144, 6144, bar + B_KV + 8 * j);
        }
        asm volatile("cp.async.bulk.prefetch.L2.global [%0], %1;" ::"l"((const uint8_t*)w2 + (size_t)bid * (FF * DM * 2 / 128)), "r"(FF * DM * 2 / 128) : "memory");
        asm volatile("cp.async.bulk.prefetch.L2.global [%0], %1;" ::"l"((const uint8_t*)wo + (size_t)bid * (DM * DM * 2 / 128)), "r"(DM * DM * 2 / 128) : "memory");
        wait_counter(&g_cnt[32], epoch * 128u);
        s = 0; ph = 1;
        #pragma unroll 1
        for (int kb = 0; kb < 34; kb++) {
          if (kb == 24) {
            wait_counter(&g_cnt[64 + 32 * (rbD >> 3)], epoch * 32u);
            if (bid == 0) g_epoch = epoch;
          }
          if (kb < 7) mbar_wait(bar + B_KVFREE + 8 * s, 0); else if (kb > 7) mbar_wait(bar + B_DEMPTY + 8 * s, ph);
          const uint32_t sa = sb + s * D_STAGE, fb = bar + B_DFULL + 8 * s;
          mbar_expect(fb, D_STAGE);
          const int kk = kb < 24 ? kb : kb - 24;
          const __nv_bfloat16* asrc = (kb < 24 ? g_hid + (size_t)((rbD >> 1) * 24 + kk) * 8192 : g_att + (size_t)((rbD >> 1) * 10 + kk) * 8192) + (rbD & 1) * 4096;
          bulk_load(sa, asrc, 8192, fb);
          tma_3d_mc(sa + 8192 + rank * 10240, kb < 24 ? &tm.w2 : &tm.wo, 0, kk * 64 + rank * 32, cbD * 5, fb, 3);
          if (++s == 8) { s = 0; ph ^= 1; }
        }
      }
    } else {
      if (warp == 19) {
        bar_sync(NB_QKV, 544);
        if (lane == 0) publish(&g_cnt[0]);
        __syncwarp();
        bar_sync(NB_HID, 544);
        if (lane == 0) publish(&g_cnt[32]);
        __syncwarp();
        bar_sync(NB_ATT, 544);
        if (lane == 0) publish(&g_cnt[64 + 32 * qq]);
        __syncwarp();
      } else {
        const int w = warp - 17, t64 = tid - 544;
        const float tag = __uint_as_float(__ldcg(&g_epoch) + 1u);
        float* s_red = reinterpret_cast<float*>(smem + SM_RED);
        auto slab_sum = [&](uint32_t fullbar, float2* dst) {
          mbar_wait(fullbar, 0);
          float a[8];
          #pragma unroll
          for (int i = 0; i < 8; i++) a[i] = 0.f;
          #pragma unroll 2
          for (int i = w; i < 40; i += 2) {
            const uint4 u = *reinterpret_cast<const uint4*>(smem + SM_SLAB + i * 512 + lane * 16);
            a[0] += bf_lo(u.x); a[1] += bf_hi(u.x); a[2] += bf_lo(u.y); a[3] += bf_hi(u.y);
            a[4] += bf_lo(u.z); a[5] += bf_hi(u.z); a[6] += bf_lo(u.w); a[7] += bf_hi(u.w);
          }
          #pragma unroll
          for (int i = 0; i < 4; i++) { const bool up = lane & 2; const float snd = up ? a[i] : a[i + 4]; a[i] = (up ? a[i + 4] : a[i]) + __shfl_xor_sync(~0u, snd, 2); }
          #pragma unroll
          for (int i = 0; i < 2; i++) { const bool up = lane & 4; const float snd = up ? a[i] : a[i + 2]; a[i] = (up ? a[i + 2] : a[i]) + __shfl_xor_sync(~0u, snd, 4); }
          { const bool up = lane & 8; const float snd = up ? a[0] : a[1]; a[0] = (up ? a[1] : a[0]) + __shfl_xor_sync(~0u, snd, 8); }
          a[0] += __shfl_xor_sync(~0u, a[0], 16);
          if (lane < 16) s_red[w * 16 + (lane & 1) * 8 + ((lane >> 1) & 1) * 4 + ((lane >> 2) & 1) * 2 + (lane >> 3)] = a[0];
          bar_sync(NB_HELP, 64);
          if (t64 < 16) st_tagged(dst + t64, s_red[t64] + s_red[16 + t64], tag);
          bar_sync(NB_HELP, 64);
        };
        if (bid < 120) slab_sum(bar + B_SLAB, g_colsum + bid * 16);
        mbar_arrive(bar + B_SLABFREE);
        {
          const float2* pc = g_colsum + cbA * 240 + t64;
          const int i3 = t64 < 48 ? 192 : 0;
          float c0, c1, c2, c3; bool ok; int spins = 0;
          do { ok = ld_tagged(pc, c0, tag); ok &= ld_tagged(pc + 64, c1, tag); ok &= ld_tagged(pc + 128, c2, tag); ok &= ld_tagged(pc + i3, c3, tag); } while (!ok && ++spins < (1 << 20));
          s_cs[t64] = c0; s_cs[64 + t64] = c1; s_cs[128 + t64] = c2; if (t64 < 48) s_cs[192 + t64] = c3;
        }
        {
          const float2* pr = g_rowstat + 2 * (rbA * 128 + t64);
          float m0, v0, m1, v1; bool ok; int spins = 0;
          do { ok = ld_tagged(pr, m0, tag); ok &= ld_tagged(pr + 1, v0, tag); ok &= ld_tagged(pr + 128, m1, tag); ok &= ld_tagged(pr + 129, v1, tag); } while (!ok && ++spins < (1 << 20));
          const float ra = 1.f / sqrtf(v0 + LN_EPS), rc = 1.f / sqrtf(v1 + LN_EPS);
          s_row[t64] = make_float4(m0, ra, ra / sqrtf(v0 * ra * ra + LN_EPS), 0.f);
          s_row[64 + t64] = make_float4(m1, rc, rc / sqrtf(v1 * rc * rc + LN_EPS), 0.f);
        }
        mbar_arrive(bar + B_PREADY);
        if (bid < 96) slab_sum(bar + B_SLAB + 8, g_colsum + NQKV + bid * 16);
        {
          const float e0 = __bfloat162float(b1[cbA * 192 + t64]), e1 = __bfloat162float(b1[cbA * 192 + 64 + t64]), e2 = __bfloat162float(b1[cbA * 192 + 128 + t64]);
          const float2* pc = g_colsum + NQKV + cbA * 192 + t64;
          float c0, c1, c2; bool ok; int spins = 0;
          do { ok = ld_tagged(pc, c0, tag); ok &= ld_tagged(pc + 64, c1, tag); ok &= ld_tagged(pc + 128, c2, tag); } while (!ok && ++spins < (1 << 20));
          s_cs1[t64] = c0; s_cs1[64 + t64] = c1; s_cs1[128 + t64] = c2;
          s_b1h[t64] = 0.5f * e0; s_b1h[64 + t64] = 0.5f * e1; s_b1h[128 + t64] = 0.5f * e2;
        }
        mbar_arrive(bar + B_PREADY + 8);
      }
    }
    cluster_sync();
    return;
  }

  asm volatile("setmaxnreg.inc.sync.aligned.u32 112;");
  const int w4 = warp & 3, g = lane >> 2, t = lane & 3;
  const int mi = wg & 1, ni = wg >> 1;
  {
    const float tag = __uint_as_float(__ldcg(&g_epoch) + 1u);
    const int row = bid * 16 + warp;
    const uint2* px = reinterpret_cast<const uint2*>(x + (size_t)row * DM);
    float v[20], sum = 0.f, sq = 0.f;
    #pragma unroll
    for (int i = 0; i < 5; i++) {
      const uint2 u = __ldg(px + i * 32 + lane);
      v[4 * i] = bf_lo(u.x); v[4 * i + 1] = bf_hi(u.x); v[4 * i + 2] = bf_lo(u.y); v[4 * i + 3] = bf_hi(u.y);
      sum += (v[4 * i] + v[4 * i + 1]) + (v[4 * i + 2] + v[4 * i + 3]);
    }
    #pragma unroll
    for (int o = 16; o; o >>= 1) sum += __shfl_xor_sync(~0u, sum, o);
    const float mean = sum * (1.f / DM);
    #pragma unroll
    for (int i = 0; i < 20; i++) { const float d = v[i] - mean; sq = fmaf(d, d, sq); }
    #pragma unroll
    for (int o = 16; o; o >>= 1) sq += __shfl_xor_sync(~0u, sq, o);
    if (lane < 2) st_tagged(g_rowstat + 2 * row + lane, lane ? sq * (1.f / DM) : mean, tag);
  }
  int s = 0; uint32_t ph = 0;
  const int tg0 = rbA * 16 + mi * 8 + w4 * 2;
  {
    float acc[60];
    #pragma unroll 1
    for (int kb = 0; kb < 10; kb++) {
      mbar_wait(bar + B_FULL + 8 * s, ph);
      const uint32_t alo = ((sd + s * AB_STAGE + mi * 8192) >> 4) | (1u << 16);
      const uint32_t blo = ((sd + s * AB_STAGE + 16384 + ni * 8192) >> 4) | (256u << 16);
      wg_fence();
      #pragma unroll
      for (int k = 0; k < 4; k++) wgmma_n120_ss(acc, alo + k * 2, 64u | (1u << 30), blo + (k >> 1) * 1024 + (k & 1) * 128, 64u | (1u << 30), (kb | k) != 0);
      wg_commit();
      if (kb > 0) { wg_wait<1>(); if (lane < 2) mbar_arrive_cta(bar + B_EMPTY + 8 * ((s + 3) & 3), lane); }
      if (++s == 4) { s = 0; ph ^= 1; }
    }
    wg_wait<0>();
    if (lane < 2) mbar_arrive_cta(bar + B_EMPTY + 8 * ((s + 3) & 3), lane);
    mbar_wait(bar + B_PREADY, 0);
    const float4 st0 = s_row[mi * 64 + w4 * 16 + g], st1 = s_row[mi * 64 + w4 * 16 + g + 8];
    const float nm0 = -st0.x, nm1 = -st1.x;
    uint32_t* dbase = reinterpret_cast<uint32_t*>(g_qkv + ((size_t)(cbA * 12 + ni * 6) * 256 + tg0) * 192) + lane;
    auto kaug = [](int grp) { return ((MUFU_MASK >> grp) & 1) ? 0u : 0x3B8043C0u; };
    const uint32_t kaug0 = kaug(tg0 & 15), kaug1 = kaug((tg0 + 1) & 15);
    #pragma unroll
    for (int pi = 0; pi < 3; pi++) {
      const int P = cbA * 6 + ni * 3 + pi, sec = P >> 4;
      const float sc = sec == 0 ? QSCALE : 1.f;
      const float r0 = st0.y * sc, r1 = st1.y * sc;
      uint32_t* de = dbase + pi * 2 * 256 * 96;
      uint32_t* dod = de + 256 * 96;
      uint32_t w[5][2];
      #pragma unroll
      for (int gi = 0; gi < 5; gi++) {
        const int i = pi * 5 + gi;
        const float2 cs = *reinterpret_cast<const float2*>(s_cs + ni * 120 + 8 * i + 2 * t);
        w[gi][0] = pack_bf16(fmaf(nm0, cs.x, acc[4 * i]) * r0, fmaf(nm0, cs.y, acc[4 * i + 1]) * r0);
        w[gi][1] = pack_bf16(fmaf(nm1, cs.x, acc[4 * i + 2]) * r1, fmaf(nm1, cs.y, acc[4 * i + 3]) * r1);
      }
      const uint32_t aug0 = sec == 1 ? kaug0 : (sec == 0 ? 0x3F803F80u : 0x00003F80u);
      const uint32_t aug1 = sec == 1 ? kaug1 : (sec == 0 ? 0x3F803F80u : 0x00003F80u);
      const uint32_t ae0 = t == 2 ? aug0 : 0u, ae1 = t == 2 ? aug1 : 0u, ao0 = t == 0 ? aug0 : 0u, ao1 = t == 0 ? aug1 : 0u;
      de[0] = w[0][0];  de[96] = w[0][1];  de[32] = w[1][0];  de[96 + 32] = w[1][1];
      de[64] = t < 2 ? w[2][0] : ae0;   de[96 + 64] = t < 2 ? w[2][1] : ae1;
      dod[0] = w[3][0]; dod[96] = w[3][1]; dod[32] = w[4][0]; dod[96 + 32] = w[4][1];
      dod[64] = t >= 2 ? w[2][0] : ao0; dod[96 + 64] = t >= 2 ? w[2][1] : ao1;
      if (sec == 1) {
        uint32_t e0 = hfma2_bf16(w[1][0], w[1][0], hmul2_bf16(w[0][0], w[0][0])), e1 = hfma2_bf16(w[1][1], w[1][1], hmul2_bf16(w[0][1], w[0][1]));
        uint32_t o0 = hfma2_bf16(w[4][0], w[4][0], hmul2_bf16(w[3][0], w[3][0])), o1 = hfma2_bf16(w[4][1], w[4][1], hmul2_bf16(w[3][1], w[3][1]));
        if (t < 2) { e0 = hfma2_bf16(w[2][0], w[2][0], e0); e1 = hfma2_bf16(w[2][1], w[2][1], e1); }
        else       { o0 = hfma2_bf16(w[2][0], w[2][0], o0); o1 = hfma2_bf16(w[2][1], w[2][1], o1); }
        float fe0 = bf_lo(e0) + bf_hi(e0), fe1 = bf_lo(e1) + bf_hi(e1), fo0 = bf_lo(o0) + bf_hi(o0), fo1 = bf_lo(o1) + bf_hi(o1);
        #pragma unroll
        for (int o = 1; o < 4; o <<= 1) {
          fe0 += __shfl_xor_sync(~0u, fe0, o); fe1 += __shfl_xor_sync(~0u, fe1, o); fo0 += __shfl_xor_sync(~0u, fo0, o); fo1 += __shfl_xor_sync(~0u, fo1, o);
        }
        const unsigned me = __reduce_max_sync(~0u, max(__float_as_uint(fe0) & 0x7FFFFFFFu, __float_as_uint(fe1) & 0x7FFFFFFFu));
        const unsigned mo = __reduce_max_sync(~0u, max(__float_as_uint(fo0) & 0x7FFFFFFFu, __float_as_uint(fo1) & 0x7FFFFFFFu));
        if (lane == 0) { float* kn = g_knorm + (size_t)(2 * P - 32) * 128 + (tg0 >> 1); kn[0] = __uint_as_float(me); kn[128] = __uint_as_float(mo); }
      } else if (sec == 2) {
        unsigned m = 0;
        #pragma unroll
        for (int gi = 0; gi < 5; gi++) m = __vmaxu2(m, __vmaxu2(w[gi][0] & 0x7FFF7FFFu, w[gi][1] & 0x7FFF7FFFu));
        m = __reduce_max_sync(~0u, max(m << 16, m & 0xFFFF0000u));
        if (lane == 0) { float* vm = g_vmax + (size_t)(2 * P - 64) * 128 + (tg0 >> 1); vm[0] = __uint_as_float(m); vm[128] = __uint_as_float(m); }
      }
    }
    asm volatile("bar.arrive %0, 544;" ::"n"(NB_QKV) : "memory");
  }
  uint32_t qa[8];
  unsigned kmax_bits, vmax_bits;
  auto load_q = [&](int tg) {
    const uint32_t* qp = reinterpret_cast<const uint32_t*>(g_qkv + ((size_t)hd * 256 + tg) * 192) + lane;
    qa[0] = __ldcg(qp); qa[1] = __ldcg(qp + 96); qa[2] = __ldcg(qp + 32); qa[3] = __ldcg(qp + 96 + 32);
    qa[4] = __ldcg(qp + 64); qa[5] = __ldcg(qp + 96 + 64); qa[6] = 0; qa[7] = 0;
    asm volatile("" : "+r"(qa[6]), "+r"(qa[7]));
  };
  {
    float acc[48];
    #pragma unroll 1
    for (int kb = 0; kb < 10; kb++) {
      mbar_wait(bar + B_FULL + 8 * s, ph);
      const uint32_t alo = ((sd + s * AB_STAGE + mi * 8192) >> 4) | (1u << 16);
      const uint32_t blo = ((sd + s * AB_STAGE + 16384 + ni * 3 * 2048) >> 4) | (128u << 16);
      wg_fence();
      #pragma unroll
      for (int k = 0; k < 4; k++) wgmma_n96_ss(acc, alo + k * 2, 64u | (1u << 30), blo + (k >> 1) * 768 + (k & 1) * 64, 32u | (2u << 30), (kb | k) != 0);
      wg_commit();
      if (kb > 0) { wg_wait<1>(); if (lane < 2) mbar_arrive_cta(bar + B_EMPTY + 8 * ((s + 3) & 3), lane); }
      if (++s == 4) { s = 0; ph ^= 1; }
    }
    wg_wait<0>();
    if (lane < 2) mbar_arrive_cta(bar + B_EMPTY + 8 * ((s + 3) & 3), lane);
    mbar_wait(bar + B_QKV, 0);
    load_q(qq * 64 + wg * 16 + w4 * 2);
    const float4 kn4 = __ldcg(reinterpret_cast<const float4*>(g_knorm + hd * 128) + lane), vm4 = __ldcg(reinterpret_cast<const float4*>(g_vmax + hd * 128) + lane);
    kmax_bits = max(max(__float_as_uint(kn4.x), __float_as_uint(kn4.y)), max(__float_as_uint(kn4.z), __float_as_uint(kn4.w)));
    vmax_bits = max(max(__float_as_uint(vm4.x), __float_as_uint(vm4.y)), max(__float_as_uint(vm4.z), __float_as_uint(vm4.w)));
    mbar_wait(bar + B_PREADY + 8, 0);
    const float4 st0 = s_row[mi * 64 + w4 * 16 + g], st1 = s_row[mi * 64 + w4 * 16 + g + 8];
    const float nm0 = -st0.x, nm1 = -st1.x, a0 = 0.5f * st0.z, a1 = 0.5f * st1.z;
    uint32_t* dst = reinterpret_cast<uint32_t*>(g_hid + ((size_t)(rbA * 24 + cbA * 3) * 16 + mi * 8 + w4 * 2) * 512) + lane;
    constexpr float GA = 1.5957691216057308f, GB = 1.5957691216057308f * 0.044715f * 4.f;
    uint32_t hw[12][2];
    #pragma unroll
    for (int i = 0; i < 12; i++) {
      const float2 cs = *reinterpret_cast<const float2*>(s_cs1 + ni * 96 + 8 * i + 2 * t);
      const float2 bb = *reinterpret_cast<const float2*>(s_b1h + ni * 96 + 8 * i + 2 * t);
      float h[4];
      h[0] = fmaf(fmaf(nm0, cs.x, acc[4 * i]), a0, bb.x);     h[1] = fmaf(fmaf(nm0, cs.y, acc[4 * i + 1]), a0, bb.y);
      h[2] = fmaf(fmaf(nm1, cs.x, acc[4 * i + 2]), a1, bb.x); h[3] = fmaf(fmaf(nm1, cs.y, acc[4 * i + 3]), a1, bb.y);
      #pragma unroll
      for (int e = 0; e < 4; e++) {
        const float u = h[e] * fmaf(h[e] * h[e], GB, GA);
        h[e] = fmaf(h[e], tanh_fast(u), h[e]);
      }
      hw[i][0] = pack_bf16(h[0], h[1]); hw[i][1] = pack_bf16(h[2], h[3]);
    }
    auto store_h = [&](auto ni_c) {
      #pragma unroll
      for (int i = 0; i < 12; i++) {
        constexpr int K0 = 12 * decltype(ni_c)::value;
        uint32_t* d = dst + ((K0 + i) >> 3) * 4096 + ((K0 + i) & 7) * 32;
        d[0] = hw[i][0]; d[256] = hw[i][1];
      }
    };
    if (ni == 0) store_h(IntC<0>{}); else store_h(IntC<1>{});
    asm volatile("bar.arrive %0, 544;" ::"n"(NB_HID) : "memory");
  }
  {
    const float kmax2 = __uint_as_float(__reduce_max_sync(~0u, kmax_bits)), vmax = __uint_as_float(__reduce_max_sync(~0u, vmax_bits));
    const bool odd = hd & 1;
    const uint32_t kv0 = sd >> 4, bb = bar + B_KV;
    constexpr uint32_t TB = KV_TILE >> 4, VOFF = (6144 >> 4) + (24u << 16);
    constexpr uint32_t FREE_MASK = (1u << 2) | (1u << 4) | (1u << 6) | (1u << 9) | (1u << 11) | (1u << 13) | (1u << 15);
    uint32_t one2 = 0x3F803F80u;
    asm volatile("" : "+r"(one2));

    #pragma unroll 1
    for (int r = 0; r < 2; r++) {
      const int tg = qq * 64 + wg * 16 + r * 8 + w4 * 2;
      if (r == 1) load_q(tg);
      const bool real2 = odd ? (t >= 2) : (t < 2);
      float n0 = bf_lo(qa[0]) * bf_lo(qa[0]) + bf_hi(qa[0]) * bf_hi(qa[0]) + bf_lo(qa[2]) * bf_lo(qa[2]) + bf_hi(qa[2]) * bf_hi(qa[2]);
      float n1 = bf_lo(qa[1]) * bf_lo(qa[1]) + bf_hi(qa[1]) * bf_hi(qa[1]) + bf_lo(qa[3]) * bf_lo(qa[3]) + bf_hi(qa[3]) * bf_hi(qa[3]);
      if (real2) { n0 += bf_lo(qa[4]) * bf_lo(qa[4]) + bf_hi(qa[4]) * bf_hi(qa[4]); n1 += bf_lo(qa[5]) * bf_lo(qa[5]) + bf_hi(qa[5]) * bf_hi(qa[5]); }
      n0 += __shfl_xor_sync(~0u, n0, 1); n0 += __shfl_xor_sync(~0u, n0, 2);
      n1 += __shfl_xor_sync(~0u, n1, 1); n1 += __shfl_xor_sync(~0u, n1, 2);
      const bool ok = (n0 * kmax2 * 1.06f <= FAST_BOUND2) && (n1 * kmax2 * 1.06f <= FAST_BOUND2) && (vmax <= FAST_VMAX);
      int allok;
      asm volatile("{\n.reg .pred p, q;\nsetp.ne.b32 p, %1, 0;\nbarrier.red.and.pred q, %2, 128, p;\nselp.b32 %0, 1, 0, q;\n}" : "=r"(allok) : "r"((int)ok), "r"(NB_WG + wg) : "memory");
      allok = __shfl_sync(~0u, allok, 0);
      float o[12];
      #pragma unroll
      for (int i = 0; i < 12; i++) o[i] = 0.f;
      int freed = 0;
      if (allok) {
        float s0[32], s1[32]; uint32_t p[16];
        if (r == 0) mbar_wait(bb, 0);
        wg_fence(); issue_qk(s0, qa, kv0); wg_commit(); wg_wait<0>();
        #pragma unroll 1
        for (int j = 0; j < 16; j++) {
          const uint32_t base = kv0 + j * TB;
          wg_fence(); issue_qk(s1, qa, base + 192u); wg_commit();
          exp_tile(s0, p, MUFU_MASK & 0xFF, one2);
          wg_fence(); issue_pv(o, p, base + VOFF); wg_commit();
          if (r == 0 && j < 15) mbar_wait(bb + (j + 1) * 8, 0);
          wg_wait<0>();
          wg_fence(); issue_qk(s0, qa, j < 15 ? base + TB : base); wg_commit();
          exp_tile(s1, p, MUFU_MASK >> 8, one2);
          wg_fence(); issue_pv(o, p, base + VOFF + 4 * 48u); wg_commit();
          wg_wait<0>();
          if (r == 1 && ((FREE_MASK >> j) & 1)) { if (lane < 2) mbar_arrive_cta(bar + B_KVFREE + 8 * freed, lane); freed++; }
        }
      } else {
        if (!real2) { qa[4] = 0; qa[5] = 0; }
        float m0 = -INFINITY, m1 = -INFINITY;
        float sc[32]; uint32_t p[16];
        #pragma unroll 1
        for (int u = 0; u < 32; u++) {
          const uint32_t base = kv0 + (u >> 1) * TB;
          mbar_wait(bb + (u >> 1) * 8, 0);
          wg_fence(); issue_qk(sc, qa, base + (u & 1) * 192u); wg_commit(); wg_wait<0>();
          float x0 = m0, x1 = m1;
          #pragma unroll
          for (int i = 0; i < 8; i++) { x0 = fmaxf(x0, fmaxf(sc[4 * i], sc[4 * i + 1])); x1 = fmaxf(x1, fmaxf(sc[4 * i + 2], sc[4 * i + 3])); }
          x0 = fmaxf(x0, __shfl_xor_sync(~0u, x0, 1)); x0 = fmaxf(x0, __shfl_xor_sync(~0u, x0, 2));
          x1 = fmaxf(x1, __shfl_xor_sync(~0u, x1, 1)); x1 = fmaxf(x1, __shfl_xor_sync(~0u, x1, 2));
          const float c0 = ex2(m0 - x0), c1 = ex2(m1 - x1);
          m0 = x0; m1 = x1;
          #pragma unroll
          for (int i = 0; i < 3; i++) { o[4 * i] *= c0; o[4 * i + 1] *= c0; o[4 * i + 2] *= c1; o[4 * i + 3] *= c1; }
          #pragma unroll
          for (int i = 0; i < 8; i++) {
            p[2 * i] = pack_bf16(ex2(sc[4 * i] - m0), ex2(sc[4 * i + 1] - m0));
            p[2 * i + 1] = pack_bf16(ex2(sc[4 * i + 2] - m1), ex2(sc[4 * i + 3] - m1));
          }
          wg_fence(); issue_pv(o, p, base + VOFF + (u & 1) * 4 * 48u); wg_commit(); wg_wait<0>();
        }
        if (r == 1 && lane < 2) for (int i = 0; i < 7; i++) mbar_arrive_cta(bar + B_KVFREE + 8 * i, lane);
      }
      const int src = (lane & ~3) | (odd ? 0 : 2);
      const float i0 = 1.f / __shfl_sync(~0u, o[8], src), i1 = 1.f / __shfl_sync(~0u, o[10], src);
      const int kg0 = (20 * hd) >> 3;
      uint32_t* ob = reinterpret_cast<uint32_t*>(g_att + ((size_t)(tg >> 4) * 10 * 16 + (tg & 15)) * 512) + lane;
      auto kaddr = [&](int kg) { return ob + (kg >> 3) * 4096 + (kg & 7) * 32; };
      uint32_t* d0 = kaddr(odd ? kg0 + 1 : kg0);
      uint32_t* d1 = kaddr(odd ? kg0 + 2 : kg0 + 1);
      uint32_t* d2 = kaddr(odd ? kg0 : kg0 + 2);
      d0[0] = pack_bf16(o[0] * i0, o[1] * i0); d0[256] = pack_bf16(o[2] * i1, o[3] * i1);
      d1[0] = pack_bf16(o[4] * i0, o[5] * i0); d1[256] = pack_bf16(o[6] * i1, o[7] * i1);
      if (real2) { d2[0] = pack_bf16(o[8] * i0, o[9] * i0); d2[256] = pack_bf16(o[10] * i1, o[11] * i1); }
    }
    asm volatile("bar.arrive %0, 544;" ::"n"(NB_ATT) : "memory");
  }
  auto phase_d = [&](auto nseg_c, auto mma, auto& acc) {
    constexpr int NSEG = decltype(nseg_c)::value;
    constexpr int NIT = NSEG / 2;
    const int col0 = cbD * 160 + wg * 96, row0 = rbD * 64 + w4 * 16;
    uint4 xv[NIT];
    #pragma unroll
    for (int it = 0; it < NIT; it++) {
      const int idx = it * 32 + lane, r = idx / NSEG, c8 = idx % NSEG;
      xv[it] = __ldg(reinterpret_cast<const uint4*>(x + (size_t)(row0 + r) * DM + col0 + c8 * 8));
    }
    int sD = 0; uint32_t phD = 0;
    #pragma unroll 1
    for (int kb = 0; kb < 34; kb++) {
      mbar_wait(bar + B_DFULL + 8 * sD, phD);
      const uint32_t alo = ((sd + sD * D_STAGE) >> 4) | (8u << 16);
      const uint32_t blo = ((sd + sD * D_STAGE + 8192 + wg * 3 * 2048) >> 4) | (128u << 16);
      wg_fence();
      #pragma unroll
      for (int k = 0; k < 4; k++) mma(acc, alo + k * 16, blo + (k >> 1) * 640 + (k & 1) * 64, (kb | k) != 0);
      wg_commit();
      if (kb > 0) { wg_wait<1>(); if (lane < 2) mbar_arrive_cta(bar + B_DEMPTY + 8 * ((sD + 7) & 7), lane); }
      if (++sD == 8) { sD = 0; phD ^= 1; }
    }
    wg_wait<0>();
    float* stg = reinterpret_cast<float*>(smem) + warp * (16 * 100);
    uint4 bv[NIT];
    #pragma unroll
    for (int it = 0; it < NIT; it++) bv[it] = __ldg(reinterpret_cast<const uint4*>(b2 + col0 + ((it * 32 + lane) % NSEG) * 8));
    bar_sync(NB_FIN, 256);
    #pragma unroll
    for (int i = 0; i < NSEG; i++) {
      *reinterpret_cast<float2*>(stg + g * 100 + 8 * i + 2 * t) = make_float2(acc[4 * i], acc[4 * i + 1]);
      *reinterpret_cast<float2*>(stg + (g + 8) * 100 + 8 * i + 2 * t) = make_float2(acc[4 * i + 2], acc[4 * i + 3]);
    }
    __syncwarp();
    #pragma unroll
    for (int it = 0; it < NIT; it++) {
      const int idx = it * 32 + lane, r = idx / NSEG, c8 = idx % NSEG;
      const float4 a0 = *reinterpret_cast<const float4*>(stg + r * 100 + c8 * 8), a1 = *reinterpret_cast<const float4*>(stg + r * 100 + c8 * 8 + 4);
      uint4 o;
      o.x = pack_bf16(a0.x + bf_lo(bv[it].x) + bf_lo(xv[it].x), a0.y + bf_hi(bv[it].x) + bf_hi(xv[it].x));
      o.y = pack_bf16(a0.z + bf_lo(bv[it].y) + bf_lo(xv[it].y), a0.w + bf_hi(bv[it].y) + bf_hi(xv[it].y));
      o.z = pack_bf16(a1.x + bf_lo(bv[it].z) + bf_lo(xv[it].z), a1.y + bf_hi(bv[it].z) + bf_hi(xv[it].z));
      o.w = pack_bf16(a1.z + bf_lo(bv[it].w) + bf_lo(xv[it].w), a1.w + bf_hi(bv[it].w) + bf_hi(xv[it].w));
      *reinterpret_cast<uint4*>(out + (size_t)(row0 + r) * DM + col0 + c8 * 8) = o;
    }
  };
  if (wg == 0) {
    float acc[48];
    phase_d(IntC<12>{}, [](float (&a)[48], uint32_t da, uint32_t db, int sc) { wgmma_n96_ss(a, da, 64u, db, 32u | (2u << 30), sc); }, acc);
  } else if (wg == 1) {
    float acc[32];
    phase_d(IntC<8>{}, [](float (&a)[32], uint32_t da, uint32_t db, int sc) { wgmma_n64_ss(a, da, 64u, db, 32u | (2u << 30), sc); }, acc);
  }
  cluster_sync();
}

typedef CUresult (*EncodeTiledFn)(CUtensorMap*, CUtensorMapDataType, cuuint32_t, void*, const cuuint64_t*, const cuuint64_t*, const cuuint32_t*,
                                  const cuuint32_t*, CUtensorMapInterleave, CUtensorMapSwizzle, CUtensorMapL2promotion, CUtensorMapFloatOOBfill);

CUtensorMap make_map(EncodeTiledFn fn, const void* base, int rank, const cuuint64_t* dims, const cuuint64_t* strides, const cuuint32_t* box, CUtensorMapSwizzle sw) {
  CUtensorMap m;
  const cuuint32_t es[4] = {1, 1, 1, 1};
  fn(&m, CU_TENSOR_MAP_DATA_TYPE_BFLOAT16, rank, const_cast<void*>(base), dims, strides, box, es, CU_TENSOR_MAP_INTERLEAVE_NONE, sw,
                   CU_TENSOR_MAP_L2_PROMOTION_L2_128B, CU_TENSOR_MAP_FLOAT_OOB_FILL_NONE);
  return m;
}

}

extern "C" void kernel_launch(void* const* d_in, const int* in_sizes, int n_in, void* d_out, int out_size) {
  const __nv_bfloat16* x = static_cast<const __nv_bfloat16*>(d_in[0]);
  const __nv_bfloat16* wqkv = static_cast<const __nv_bfloat16*>(d_in[1]);
  const __nv_bfloat16* wo = static_cast<const __nv_bfloat16*>(d_in[2]);
  const __nv_bfloat16* w1 = static_cast<const __nv_bfloat16*>(d_in[4]);
  const __nv_bfloat16* b1 = static_cast<const __nv_bfloat16*>(d_in[5]);
  const __nv_bfloat16* w2 = static_cast<const __nv_bfloat16*>(d_in[6]);
  const __nv_bfloat16* b2 = static_cast<const __nv_bfloat16*>(d_in[7]);
  __nv_bfloat16* out = static_cast<__nv_bfloat16*>(d_out);

  static EncodeTiledFn encode = nullptr;
  if (!encode) {
    void* fn = nullptr;
    cudaDriverEntryPointQueryResult qr;
    cudaGetDriverEntryPoint("cuTensorMapEncodeTiled", &fn, cudaEnableDefault, &qr);
    encode = reinterpret_cast<EncodeTiledFn>(fn);
    cudaFuncSetAttribute(fused_block, cudaFuncAttributeMaxDynamicSharedMemorySize, SMEM_BYTES);
  }
  Maps tm;
  { const cuuint64_t d[2] = {DM, S_LEN}, st[1] = {DM * 2}; const cuuint32_t b[2] = {64, 128}; tm.x = make_map(encode, x, 2, d, st, b, CU_TENSOR_MAP_SWIZZLE_128B); }
  { const cuuint64_t d[2] = {NQKV, DM}, st[1] = {NQKV * 2}; const cuuint32_t b[2] = {64, 32}; tm.wqkv = make_map(encode, wqkv, 2, d, st, b, CU_TENSOR_MAP_SWIZZLE_128B); }
  { const cuuint64_t d[4] = {64, DM, 2, 16}, st[3] = {NQKV * 2, 128, 240}; const cuuint32_t b[4] = {64, 32, 2, 2}; tm.wq4 = make_map(encode, wqkv, 4, d, st, b, CU_TENSOR_MAP_SWIZZLE_128B); }
  { const cuuint64_t d[3] = {32, DM, FF / 32}, st[2] = {FF * 2, 64}; const cuuint32_t b[3] = {32, 32, 6}; tm.w1 = make_map(encode, w1, 3, d, st, b, CU_TENSOR_MAP_SWIZZLE_64B); }
  { const cuuint64_t d[2] = {NQKV, DM}, st[1] = {NQKV * 2}; const cuuint32_t b[2] = {16, 160}; tm.sq = make_map(encode, wqkv, 2, d, st, b, CU_TENSOR_MAP_SWIZZLE_NONE); }
  { const cuuint64_t d[2] = {FF, DM}, st[1] = {FF * 2}; const cuuint32_t b[2] = {16, 160}; tm.s1 = make_map(encode, w1, 2, d, st, b, CU_TENSOR_MAP_SWIZZLE_NONE); }
  { const cuuint64_t d[3] = {32, FF, DM / 32}, st[2] = {DM * 2, 64}; const cuuint32_t b[3] = {32, 32, 5}; tm.w2 = make_map(encode, w2, 3, d, st, b, CU_TENSOR_MAP_SWIZZLE_64B); }
  { const cuuint64_t d[3] = {32, DM, DM / 32}, st[2] = {DM * 2, 64}; const cuuint32_t b[3] = {32, 32, 5}; tm.wo = make_map(encode, wo, 3, d, st, b, CU_TENSOR_MAP_SWIZZLE_64B); }

  cudaLaunchAttribute at[1];
  at[0].id = cudaLaunchAttributeClusterDimension; at[0].val.clusterDim.x = 2; at[0].val.clusterDim.y = 1; at[0].val.clusterDim.z = 1;
  cudaLaunchConfig_t cfg = {};
  cfg.stream = cudaStreamPerThread;
  cfg.gridDim = dim3(128); cfg.blockDim = dim3(640); cfg.dynamicSmemBytes = SMEM_BYTES; cfg.attrs = at; cfg.numAttrs = 1;
  cudaLaunchKernelEx(&cfg, fused_block, tm, x, wqkv, w1, b1, w2, wo, b2, out);
}
```
